```python
import torch

def _softmax(x, axis=-1):
    return torch.softmax(x, dim=axis)
def _gelu(x):
    return torch.nn.functional.gelu(x, approximate="tanh")
def _silu(x):
    return torch.nn.functional.silu(x)
def _sigmoid(x):
    return torch.sigmoid(x)
def _layernorm(x, axis=-1, eps=1e-5):
    m = x.mean(dim=axis, keepdim=True)
    v = x.var(dim=axis, keepdim=True, unbiased=False)
    return (x - m) / torch.sqrt(v + eps)
def _scatter_add(tgt, idx, src, axis=0):
    return tgt.clone().index_add_(axis, idx, src)
def _segment_sum(src, seg, n):
    out = torch.zeros((n,) + src.shape[1:], dtype=src.dtype)
    return out.index_add_(0, seg, src)
def _pad(x, pw):
    flat = tuple(v for pair in reversed(pw) for v in pair)
    return torch.nn.functional.pad(x, flat)

kernel_name = 'sequential_preLN__spectral_gfnet__dense_activation_silu__prompt'

def setup_inputs():

    _w = (lambda a: (lambda t: t.to(torch.bfloat16) if t.is_floating_point() else t)(torch.as_tensor(a)))
    def _A_setup():
        B, S, D = 1, 2048, 512
        Df = D // 2 + 1
        return {
            "x": _w((lambda *s: torch.randn(*s, dtype=torch.bfloat16) * 0.05)(B, S, D)),
            "w_r": _w((lambda *s: torch.randn(*s, dtype=torch.bfloat16) * 0.4)(S, Df) * 0.02),
            "w_i": _w((lambda *s: torch.randn(*s, dtype=torch.bfloat16) * 0.4)(S, Df) * 0.02),
        }
    _A_in = _A_setup()

    def _B_setup():
        B, S, D, F = 1, 2048, 512, 1792
        return {
            "x": _w((lambda *s: torch.randn(*s, dtype=torch.bfloat16) * 0.05)(B, S, D)),
            "w1": _w((lambda *s: torch.randn(*s, dtype=torch.bfloat16) * 0.8)(D, F) * (D ** -0.5)),
            "w2": _w((lambda *s: torch.randn(*s, dtype=torch.bfloat16) * 0.1)(F, D) * (F ** -0.5)),
        }
    _B_in = _B_setup()

    return {
        "A_x": _A_in["x"],
        "A_w_r": _A_in["w_r"],
        "A_w_i": _A_in["w_i"],
        "B_x": _B_in["x"],
        "B_w1": _B_in["w1"],
        "B_w2": _B_in["w2"],
    }

def reference(A_x, A_w_r, A_w_i, B_x, B_w1, B_w2):
    def _A_ref(x, w_r, w_i):
        B, S, D = x.shape
        X = (lambda x, axes=(-2,-1): torch.fft.rfft2(x.float(), dim=axes))(x, axes=(-2, -1))
        W = w_r + 1j * w_i
        X = X * W
        y = (lambda x, s, axes=(-2,-1): torch.fft.irfft2(x, s=s, dim=axes).to(torch.bfloat16))(X, (S, D), axes=(-2, -1))
        return y

    def _B_ref(x, w1, w2):
        h = torch.einsum("bsd,df->bsf", x, w1)
        h = _silu(h)
        out = torch.einsum("bsf,fd->bsd", h, w2)
        return out

    x = A_x
    h = x + _A_ref(_layernorm(x, axis=-1), A_w_r, A_w_i)
    h2 = h + _B_ref(_layernorm(h, axis=-1), B_w1, B_w2)
    return h2
```

```cpp
#include <cuda_runtime.h>
#include <cuda_bf16.h>
#include <cuda_fp16.h>
#include <cuda.h>
#include <stdint.h>

__device__ __align__(128) const uint32_t c_frag[10240] = {
0x3c003c00,0x80008000,0x3c003c00,0x80008000,0x3c003c00,0x80008000,0x3c003c00,0x80008000,0x3c003c00,0x80008000,0x3c003c00,0x80008000,0x3c003c00,0x80008000,0x3c003c00,0x80008000,
0x3bd93c00,0xb23e8000,0xb23e0000,0xbbd9bc00,0x3aa73b64,0xb872b61f,0xb872b61f,0xbaa7bb64,0x387239a8,0xbaa7b9a8,0xbaa7b9a8,0xb872b9a8,0x323e361f,0xbbd9bb64,0xbbd9bb64,0xb23eb61f,
0x3b643c00,0xb61f8000,0xbb64bc00,0x361f8000,0x361f39a8,0xbb64b9a8,0xb61fb9a8,0x3b6439a8,0xb61f0000,0xbb64bc00,0x361f0000,0x3b643c00,0xbb64b9a8,0xb61fb9a8,0x3b6439a8,0x361f39a8,
0x3aa73c00,0xb8728000,0x38720000,0x3aa73c00,0xb23e361f,0xbbd9bb64,0x3bd93b64,0xb23e361f,0xbbd9b9a8,0xb23eb9a8,0x323e39a8,0xbbd9b9a8,0xb872bb64,0x3aa7361f,0xbaa7b61f,0xb872bb64,
0x39a83c00,0xb9a88000,0x39a83c00,0xb9a88000,0xb9a80000,0xb9a8bc00,0xb9a80000,0xb9a8bc00,0xb9a8bc00,0x39a88000,0xb9a8bc00,0x39a88000,0x39a80000,0x39a83c00,0x39a80000,0x39a83c00,
0x38723c00,0xbaa78000,0xbaa70000,0xb872bc00,0xbbd9b61f,0xb23ebb64,0xb23ebb64,0x3bd9361f,0x323eb9a8,0x3bd939a8,0x3bd939a8,0xb23e39a8,0x3aa73b64,0xb872361f,0xb872361f,0xbaa7bb64,
0x361f3c00,0xbb648000,0xb61fbc00,0x3b648000,0xbb64b9a8,0x361fb9a8,0x3b6439a8,0xb61f39a8,0x3b640000,0x361f3c00,0xbb640000,0xb61fbc00,0xb61f39a8,0xbb64b9a8,0x361fb9a8,0x3b6439a8,
0x323e3c00,0xbbd98000,0x3bd90000,0x323e3c00,0xb872bb64,0x3aa7b61f,0xbaa7361f,0xb872bb64,0x3aa739a8,0xb87239a8,0x3872b9a8,0x3aa739a8,0xbbd9b61f,0x323ebb64,0xb23e3b64,0xbbd9b61f,
0x3c00,0xbc008000,0x3c00,0xbc008000,0xbc00,0x3c008000,0xbc00,0x3c008000,0x3c00,0xbc008000,0x3c00,0xbc008000,0xbc00,0x3c008000,0xbc00,0x3c008000,
0xb23e3c00,0xbbd98000,0xbbd90000,0x323ebc00,0x3872bb64,0x3aa7361f,0x3aa7361f,0xb8723b64,0xbaa739a8,0xb872b9a8,0xb872b9a8,0x3aa7b9a8,0x3bd9b61f,0x323e3b64,0x323e3b64,0xbbd9361f,
0xb61f3c00,0xbb648000,0x361fbc00,0x3b648000,0x3b64b9a8,0x361f39a8,0xbb6439a8,0xb61fb9a8,0xbb640000,0x361fbc00,0x3b640000,0xb61f3c00,0x361f39a8,0xbb6439a8,0xb61fb9a8,0x3b64b9a8,
0xb8723c00,0xbaa78000,0x3aa70000,0xb8723c00,0x3bd9b61f,0xb23e3b64,0x323ebb64,0x3bd9b61f,0xb23eb9a8,0x3bd9b9a8,0xbbd939a8,0xb23eb9a8,0xbaa73b64,0xb872b61f,0x3872361f,0xbaa73b64,
0xb9a83c00,0xb9a88000,0xb9a83c00,0xb9a88000,0x39a80000,0xb9a83c00,0x39a80000,0xb9a83c00,0x39a8bc00,0x39a88000,0x39a8bc00,0x39a88000,0xb9a80000,0x39a8bc00,0xb9a80000,0x39a8bc00,
0xbaa73c00,0xb8728000,0xb8720000,0x3aa7bc00,0x323e361f,0xbbd93b64,0xbbd93b64,0xb23eb61f,0x3bd9b9a8,0xb23e39a8,0xb23e39a8,0xbbd939a8,0x3872bb64,0x3aa7b61f,0x3aa7b61f,0xb8723b64,
0xbb643c00,0xb61f8000,0x3b64bc00,0x361f8000,0xb61f39a8,0xbb6439a8,0x361fb9a8,0x3b64b9a8,0x361f0000,0xbb643c00,0xb61f0000,0x3b64bc00,0x3b64b9a8,0xb61f39a8,0xbb6439a8,0x361fb9a8,
0xbbd93c00,0xb23e8000,0x323e0000,0xbbd93c00,0xbaa73b64,0xb872361f,0x3872b61f,0xbaa73b64,0xb87239a8,0xbaa739a8,0x3aa7b9a8,0xb87239a8,0xb23e361f,0xbbd93b64,0x3bd9bb64,0xb23e361f,
0xbc003c00,0x80008000,0xbc003c00,0x80008000,0xbc003c00,0x80008000,0xbc003c00,0x80008000,0xbc003c00,0x80008000,0xbc003c00,0x80008000,0xbc003c00,0x80008000,0xbc003c00,0x80008000,
0xbbd93c00,0x323e8000,0x323e0000,0x3bd9bc00,0xbaa73b64,0x3872b61f,0x3872b61f,0x3aa7bb64,0xb87239a8,0x3aa7b9a8,0x3aa7b9a8,0x3872b9a8,0xb23e361f,0x3bd9bb64,0x3bd9bb64,0x323eb61f,
0xbb643c00,0x361f8000,0x3b64bc00,0xb61f8000,0xb61f39a8,0x3b64b9a8,0x361fb9a8,0xbb6439a8,0x361f0000,0x3b64bc00,0xb61f0000,0xbb643c00,0x3b64b9a8,0x361fb9a8,0xbb6439a8,0xb61f39a8,
0xbaa73c00,0x38728000,0xb8720000,0xbaa73c00,0x323e361f,0x3bd9bb64,0xbbd93b64,0x323e361f,0x3bd9b9a8,0x323eb9a8,0xb23e39a8,0x3bd9b9a8,0x3872bb64,0xbaa7361f,0x3aa7b61f,0x3872bb64,
0xb9a83c00,0x39a88000,0xb9a83c00,0x39a88000,0x39a80000,0x39a8bc00,0x39a80000,0x39a8bc00,0x39a8bc00,0xb9a88000,0x39a8bc00,0xb9a88000,0xb9a80000,0xb9a83c00,0xb9a80000,0xb9a83c00,
0xb8723c00,0x3aa78000,0x3aa70000,0x3872bc00,0x3bd9b61f,0x323ebb64,0x323ebb64,0xbbd9361f,0xb23eb9a8,0xbbd939a8,0xbbd939a8,0x323e39a8,0xbaa73b64,0x3872361f,0x3872361f,0x3aa7bb64,
0xb61f3c00,0x3b648000,0x361fbc00,0xbb648000,0x3b64b9a8,0xb61fb9a8,0xbb6439a8,0x361f39a8,0xbb640000,0xb61f3c00,0x3b640000,0x361fbc00,0x361f39a8,0x3b64b9a8,0xb61fb9a8,0xbb6439a8,
0xb23e3c00,0x3bd98000,0xbbd90000,0xb23e3c00,0x3872bb64,0xbaa7b61f,0x3aa7361f,0x3872bb64,0xbaa739a8,0x387239a8,0xb872b9a8,0xbaa739a8,0x3bd9b61f,0xb23ebb64,0x323e3b64,0x3bd9b61f,
0x3c00,0x3c008000,0x3c00,0x3c008000,0xbc00,0xbc008000,0xbc00,0xbc008000,0x3c00,0x3c008000,0x3c00,0x3c008000,0xbc00,0xbc008000,0xbc00,0xbc008000,
0x323e3c00,0x3bd98000,0x3bd90000,0xb23ebc00,0xb872bb64,0xbaa7361f,0xbaa7361f,0x38723b64,0x3aa739a8,0x3872b9a8,0x3872b9a8,0xbaa7b9a8,0xbbd9b61f,0xb23e3b64,0xb23e3b64,0x3bd9361f,
0x361f3c00,0x3b648000,0xb61fbc00,0xbb648000,0xbb64b9a8,0xb61f39a8,0x3b6439a8,0x361fb9a8,0x3b640000,0xb61fbc00,0xbb640000,0x361f3c00,0xb61f39a8,0x3b6439a8,0x361fb9a8,0xbb64b9a8,
0x38723c00,0x3aa78000,0xbaa70000,0x38723c00,0xbbd9b61f,0x323e3b64,0xb23ebb64,0xbbd9b61f,0x323eb9a8,0xbbd9b9a8,0x3bd939a8,0x323eb9a8,0x3aa73b64,0x3872b61f,0xb872361f,0x3aa73b64,
0x39a83c00,0x39a88000,0x39a83c00,0x39a88000,0xb9a80000,0x39a83c00,0xb9a80000,0x39a83c00,0xb9a8bc00,0xb9a88000,0xb9a8bc00,0xb9a88000,0x39a80000,0xb9a8bc00,0x39a80000,0xb9a8bc00,
0x3aa73c00,0x38728000,0x38720000,0xbaa7bc00,0xb23e361f,0x3bd93b64,0x3bd93b64,0x323eb61f,0xbbd9b9a8,0x323e39a8,0x323e39a8,0x3bd939a8,0xb872bb64,0xbaa7b61f,0xbaa7b61f,0x38723b64,
0x3b643c00,0x361f8000,0xbb64bc00,0xb61f8000,0x361f39a8,0x3b6439a8,0xb61fb9a8,0xbb64b9a8,0xb61f0000,0x3b643c00,0x361f0000,0xbb64bc00,0xbb64b9a8,0x361f39a8,0x3b6439a8,0xb61fb9a8,
0x3bd93c00,0x323e8000,0xb23e0000,0x3bd93c00,0x3aa73b64,0x3872361f,0xb872b61f,0x3aa73b64,0x387239a8,0x3aa739a8,0xbaa7b9a8,0x387239a8,0x323e361f,0x3bd93b64,0xbbd9bb64,0x323e361f,
0x3c003c00,0x80008000,0x3c003c00,0x80008000,0x3c003c00,0x80008000,0x3c003c00,0x80008000,0x3c003c00,0x80008000,0x3c003c00,0x80008000,0x3c003c00,0x80008000,0x3c003c00,0x80008000,
0xbbd9bc00,0x323e8000,0x323e0000,0x3bd93c00,0xbaa7bb64,0x3872361f,0x3872361f,0x3aa73b64,0xb872b9a8,0x3aa739a8,0x3aa739a8,0x387239a8,0xb23eb61f,0x3bd93b64,0x3bd93b64,0x323e361f,
0x3b643c00,0xb61f8000,0xbb64bc00,0x361f8000,0x361f39a8,0xbb64b9a8,0xb61fb9a8,0x3b6439a8,0xb61f0000,0xbb64bc00,0x361f0000,0x3b643c00,0xbb64b9a8,0xb61fb9a8,0x3b6439a8,0x361f39a8,
0xbaa7bc00,0x38728000,0xb8720000,0xbaa7bc00,0x323eb61f,0x3bd93b64,0xbbd9bb64,0x323eb61f,0x3bd939a8,0x323e39a8,0xb23eb9a8,0x3bd939a8,0x38723b64,0xbaa7b61f,0x3aa7361f,0x38723b64,
0x39a83c00,0xb9a88000,0x39a83c00,0xb9a88000,0xb9a80000,0xb9a8bc00,0xb9a80000,0xb9a8bc00,0xb9a8bc00,0x39a88000,0xb9a8bc00,0x39a88000,0x39a80000,0x39a83c00,0x39a80000,0x39a83c00,
0xb872bc00,0x3aa78000,0x3aa70000,0x38723c00,0x3bd9361f,0x323e3b64,0x323e3b64,0xbbd9b61f,0xb23e39a8,0xbbd9b9a8,0xbbd9b9a8,0x323eb9a8,0xbaa7bb64,0x3872b61f,0x3872b61f,0x3aa73b64,
0x361f3c00,0xbb648000,0xb61fbc00,0x3b648000,0xbb64b9a8,0x361fb9a8,0x3b6439a8,0xb61f39a8,0x3b640000,0x361f3c00,0xbb640000,0xb61fbc00,0xb61f39a8,0xbb64b9a8,0x361fb9a8,0x3b6439a8,
0xb23ebc00,0x3bd98000,0xbbd90000,0xb23ebc00,0x38723b64,0xbaa7361f,0x3aa7b61f,0x38723b64,0xbaa7b9a8,0x3872b9a8,0xb87239a8,0xbaa7b9a8,0x3bd9361f,0xb23e3b64,0x323ebb64,0x3bd9361f,
0x3c00,0xbc008000,0x3c00,0xbc008000,0xbc00,0x3c008000,0xbc00,0x3c008000,0x3c00,0xbc008000,0x3c00,0xbc008000,0xbc00,0x3c008000,0xbc00,0x3c008000,
0x323ebc00,0x3bd98000,0x3bd90000,0xb23e3c00,0xb8723b64,0xbaa7b61f,0xbaa7b61f,0x3872bb64,0x3aa7b9a8,0x387239a8,0x387239a8,0xbaa739a8,0xbbd9361f,0xb23ebb64,0xb23ebb64,0x3bd9b61f,
0xb61f3c00,0xbb648000,0x361fbc00,0x3b648000,0x3b64b9a8,0x361f39a8,0xbb6439a8,0xb61fb9a8,0xbb640000,0x361fbc00,0x3b640000,0xb61f3c00,0x361f39a8,0xbb6439a8,0xb61fb9a8,0x3b64b9a8,
0x3872bc00,0x3aa78000,0xbaa70000,0x3872bc00,0xbbd9361f,0x323ebb64,0xb23e3b64,0xbbd9361f,0x323e39a8,0xbbd939a8,0x3bd9b9a8,0x323e39a8,0x3aa7bb64,0x3872361f,0xb872b61f,0x3aa7bb64,
0xb9a83c00,0xb9a88000,0xb9a83c00,0xb9a88000,0x39a80000,0xb9a83c00,0x39a80000,0xb9a83c00,0x39a8bc00,0x39a88000,0x39a8bc00,0x39a88000,0xb9a80000,0x39a8bc00,0xb9a80000,0x39a8bc00,
0x3aa7bc00,0x38728000,0x38720000,0xbaa73c00,0xb23eb61f,0x3bd9bb64,0x3bd9bb64,0x323e361f,0xbbd939a8,0x323eb9a8,0x323eb9a8,0x3bd9b9a8,0xb8723b64,0xbaa7361f,0xbaa7361f,0x3872bb64,
0xbb643c00,0xb61f8000,0x3b64bc00,0x361f8000,0xb61f39a8,0xbb6439a8,0x361fb9a8,0x3b64b9a8,0x361f0000,0xbb643c00,0xb61f0000,0x3b64bc00,0x3b64b9a8,0xb61f39a8,0xbb6439a8,0x361fb9a8,
0x3bd9bc00,0x323e8000,0xb23e0000,0x3bd9bc00,0x3aa7bb64,0x3872b61f,0xb872361f,0x3aa7bb64,0x3872b9a8,0x3aa7b9a8,0xbaa739a8,0x3872b9a8,0x323eb61f,0x3bd9bb64,0xbbd93b64,0x323eb61f,
0xbc003c00,0x80008000,0xbc003c00,0x80008000,0xbc003c00,0x80008000,0xbc003c00,0x80008000,0xbc003c00,0x80008000,0xbc003c00,0x80008000,0xbc003c00,0x80008000,0xbc003c00,0x80008000,
0x3bd9bc00,0xb23e8000,0xb23e0000,0xbbd93c00,0x3aa7bb64,0xb872361f,0xb872361f,0xbaa73b64,0x3872b9a8,0xbaa739a8,0xbaa739a8,0xb87239a8,0x323eb61f,0xbbd93b64,0xbbd93b64,0xb23e361f,
0xbb643c00,0x361f8000,0x3b64bc00,0xb61f8000,0xb61f39a8,0x3b64b9a8,0x361fb9a8,0xbb6439a8,0x361f0000,0x3b64bc00,0xb61f0000,0xbb643c00,0x3b64b9a8,0x361fb9a8,0xbb6439a8,0xb61f39a8,
0x3aa7bc00,0xb8728000,0x38720000,0x3aa7bc00,0xb23eb61f,0xbbd93b64,0x3bd9bb64,0xb23eb61f,0xbbd939a8,0xb23e39a8,0x323eb9a8,0xbbd939a8,0xb8723b64,0x3aa7b61f,0xbaa7361f,0xb8723b64,
0xb9a83c00,0x39a88000,0xb9a83c00,0x39a88000,0x39a80000,0x39a8bc00,0x39a80000,0x39a8bc00,0x39a8bc00,0xb9a88000,0x39a8bc00,0xb9a88000,0xb9a80000,0xb9a83c00,0xb9a80000,0xb9a83c00,
0x3872bc00,0xbaa78000,0xbaa70000,0xb8723c00,0xbbd9361f,0xb23e3b64,0xb23e3b64,0x3bd9b61f,0x323e39a8,0x3bd9b9a8,0x3bd9b9a8,0xb23eb9a8,0x3aa7bb64,0xb872b61f,0xb872b61f,0xbaa73b64,
0xb61f3c00,0x3b648000,0x361fbc00,0xbb648000,0x3b64b9a8,0xb61fb9a8,0xbb6439a8,0x361f39a8,0xbb640000,0xb61f3c00,0x3b640000,0x361fbc00,0x361f39a8,0x3b64b9a8,0xb61fb9a8,0xbb6439a8,
0x323ebc00,0xbbd98000,0x3bd90000,0x323ebc00,0xb8723b64,0x3aa7361f,0xbaa7b61f,0xb8723b64,0x3aa7b9a8,0xb872b9a8,0x387239a8,0x3aa7b9a8,0xbbd9361f,0x323e3b64,0xb23ebb64,0xbbd9361f,
0x3c00,0x3c008000,0x3c00,0x3c008000,0xbc00,0xbc008000,0xbc00,0xbc008000,0x3c00,0x3c008000,0x3c00,0x3c008000,0xbc00,0xbc008000,0xbc00,0xbc008000,
0xb23ebc00,0xbbd98000,0xbbd90000,0x323e3c00,0x38723b64,0x3aa7b61f,0x3aa7b61f,0xb872bb64,0xbaa7b9a8,0xb87239a8,0xb87239a8,0x3aa739a8,0x3bd9361f,0x323ebb64,0x323ebb64,0xbbd9b61f,
0x361f3c00,0x3b648000,0xb61fbc00,0xbb648000,0xbb64b9a8,0xb61f39a8,0x3b6439a8,0x361fb9a8,0x3b640000,0xb61fbc00,0xbb640000,0x361f3c00,0xb61f39a8,0x3b6439a8,0x361fb9a8,0xbb64b9a8,
0xb872bc00,0xbaa78000,0x3aa70000,0xb872bc00,0x3bd9361f,0xb23ebb64,0x323e3b64,0x3bd9361f,0xb23e39a8,0x3bd939a8,0xbbd9b9a8,0xb23e39a8,0xbaa7bb64,0xb872361f,0x3872b61f,0xbaa7bb64,
0x39a83c00,0x39a88000,0x39a83c00,0x39a88000,0xb9a80000,0x39a83c00,0xb9a80000,0x39a83c00,0xb9a8bc00,0xb9a88000,0xb9a8bc00,0xb9a88000,0x39a80000,0xb9a8bc00,0x39a80000,0xb9a8bc00,
0xbaa7bc00,0xb8728000,0xb8720000,0x3aa73c00,0x323eb61f,0xbbd9bb64,0xbbd9bb64,0xb23e361f,0x3bd939a8,0xb23eb9a8,0xb23eb9a8,0xbbd9b9a8,0x38723b64,0x3aa7361f,0x3aa7361f,0xb872bb64,
0x3b643c00,0x361f8000,0xbb64bc00,0xb61f8000,0x361f39a8,0x3b6439a8,0xb61fb9a8,0xbb64b9a8,0xb61f0000,0x3b643c00,0x361f0000,0xbb64bc00,0xbb64b9a8,0x361f39a8,0x3b6439a8,0xb61fb9a8,
0xbbd9bc00,0xb23e8000,0x323e0000,0xbbd9bc00,0xbaa7bb64,0xb872b61f,0x3872361f,0xbaa7bb64,0xb872b9a8,0xbaa7b9a8,0x3aa739a8,0xb872b9a8,0xb23eb61f,0xbbd9bb64,0x3bd93b64,0xb23eb61f,
0,0x3c003c00,0,0x3c003c00,0,0x3c003c00,0,0x3c003c00,0,0x3c003c00,0,0x3c003c00,0,0x3c003c00,0,0x3c003c00,
0x323e0000,0x3bd93c00,0x3bd93c00,0xb23e0000,0x3872361f,0x3aa73b64,0x3aa73b64,0xb872b61f,0x3aa739a8,0x387239a8,0x387239a8,0xbaa7b9a8,0x3bd93b64,0x323e361f,0x323e361f,0xbbd9bb64,
0x361f0000,0x3b643c00,0xb61f0000,0xbb64bc00,0x3b6439a8,0x361f39a8,0xbb64b9a8,0xb61fb9a8,0x3b643c00,0xb61f0000,0xbb64bc00,0x361f0000,0x361f39a8,0xbb64b9a8,0xb61fb9a8,0x3b6439a8,
0x38720000,0x3aa73c00,0xbaa7bc00,0x38720000,0x3bd93b64,0xb23e361f,0x323eb61f,0x3bd93b64,0x323e39a8,0xbbd9b9a8,0x3bd939a8,0x323e39a8,0xbaa7b61f,0xb872bb64,0x38723b64,0xbaa7b61f,
0x39a80000,0x39a83c00,0x39a80000,0x39a83c00,0x39a83c00,0xb9a80000,0x39a83c00,0xb9a80000,0xb9a80000,0xb9a8bc00,0xb9a80000,0xb9a8bc00,0xb9a8bc00,0x39a80000,0xb9a8bc00,0x39a80000,
0x3aa70000,0x38723c00,0x38723c00,0xbaa70000,0x323e3b64,0xbbd9b61f,0xbbd9b61f,0xb23ebb64,0xbbd9b9a8,0x323eb9a8,0x323eb9a8,0x3bd939a8,0x3872b61f,0x3aa73b64,0x3aa73b64,0xb872361f,
0x3b640000,0x361f3c00,0xbb640000,0xb61fbc00,0xb61f39a8,0xbb64b9a8,0x361fb9a8,0x3b6439a8,0xb61fbc00,0x3b640000,0x361f3c00,0xbb640000,0x3b6439a8,0xb61f39a8,0xbb64b9a8,0x361fb9a8,
0x3bd90000,0x323e3c00,0xb23ebc00,0x3bd90000,0xbaa7361f,0xb872bb64,0x38723b64,0xbaa7361f,0x3872b9a8,0x3aa739a8,0xbaa7b9a8,0x3872b9a8,0xb23e3b64,0xbbd9b61f,0x3bd9361f,0xb23e3b64,
0x3c000000,0x3c00,0x3c000000,0x3c00,0xbc000000,0xbc00,0xbc000000,0xbc00,0x3c000000,0x3c00,0x3c000000,0x3c00,0xbc000000,0xbc00,0xbc000000,0xbc00,
0x3bd90000,0xb23e3c00,0xb23e3c00,0xbbd90000,0xbaa7b61f,0x3872bb64,0x3872bb64,0x3aa7361f,0x387239a8,0xbaa739a8,0xbaa739a8,0xb872b9a8,0xb23ebb64,0x3bd9b61f,0x3bd9b61f,0x323e3b64,
0x3b640000,0xb61f3c00,0xbb640000,0x361fbc00,0xb61fb9a8,0x3b64b9a8,0x361f39a8,0xbb6439a8,0xb61f3c00,0xbb640000,0x361fbc00,0x3b640000,0x3b64b9a8,0x361f39a8,0xbb6439a8,0xb61fb9a8,
0x3aa70000,0xb8723c00,0x3872bc00,0x3aa70000,0x323ebb64,0x3bd9b61f,0xbbd9361f,0x323ebb64,0xbbd939a8,0xb23eb9a8,0x323e39a8,0xbbd939a8,0x3872361f,0xbaa73b64,0x3aa7bb64,0x3872361f,
0x39a80000,0xb9a83c00,0x39a80000,0xb9a83c00,0x39a8bc00,0x39a80000,0x39a8bc00,0x39a80000,0xb9a80000,0x39a8bc00,0xb9a80000,0x39a8bc00,0xb9a83c00,0xb9a80000,0xb9a83c00,0xb9a80000,
0x38720000,0xbaa73c00,0xbaa73c00,0xb8720000,0x3bd9bb64,0x323e361f,0x323e361f,0xbbd93b64,0x323eb9a8,0x3bd9b9a8,0x3bd9b9a8,0xb23e39a8,0xbaa7361f,0x3872bb64,0x3872bb64,0x3aa7b61f,
0x361f0000,0xbb643c00,0xb61f0000,0x3b64bc00,0x3b64b9a8,0xb61f39a8,0xbb6439a8,0x361fb9a8,0x3b64bc00,0x361f0000,0xbb643c00,0xb61f0000,0x361fb9a8,0x3b64b9a8,0xb61f39a8,0xbb6439a8,
0x323e0000,0xbbd93c00,0x3bd9bc00,0x323e0000,0x3872b61f,0xbaa73b64,0x3aa7bb64,0x3872b61f,0x3aa7b9a8,0xb87239a8,0x3872b9a8,0x3aa7b9a8,0x3bd9bb64,0xb23e361f,0x323eb61f,0x3bd9bb64,
0,0xbc003c00,0,0xbc003c00,0,0xbc003c00,0,0xbc003c00,0,0xbc003c00,0,0xbc003c00,0,0xbc003c00,0,0xbc003c00,
0xb23e0000,0xbbd93c00,0xbbd93c00,0x323e0000,0xb872361f,0xbaa73b64,0xbaa73b64,0x3872b61f,0xbaa739a8,0xb87239a8,0xb87239a8,0x3aa7b9a8,0xbbd93b64,0xb23e361f,0xb23e361f,0x3bd9bb64,
0xb61f0000,0xbb643c00,0x361f0000,0x3b64bc00,0xbb6439a8,0xb61f39a8,0x3b64b9a8,0x361fb9a8,0xbb643c00,0x361f0000,0x3b64bc00,0xb61f0000,0xb61f39a8,0x3b64b9a8,0x361fb9a8,0xbb6439a8,
0xb8720000,0xbaa73c00,0x3aa7bc00,0xb8720000,0xbbd93b64,0x323e361f,0xb23eb61f,0xbbd93b64,0xb23e39a8,0x3bd9b9a8,0xbbd939a8,0xb23e39a8,0x3aa7b61f,0x3872bb64,0xb8723b64,0x3aa7b61f,
0xb9a80000,0xb9a83c00,0xb9a80000,0xb9a83c00,0xb9a83c00,0x39a80000,0xb9a83c00,0x39a80000,0x39a80000,0x39a8bc00,0x39a80000,0x39a8bc00,0x39a8bc00,0xb9a80000,0x39a8bc00,0xb9a80000,
0xbaa70000,0xb8723c00,0xb8723c00,0x3aa70000,0xb23e3b64,0x3bd9b61f,0x3bd9b61f,0x323ebb64,0x3bd9b9a8,0xb23eb9a8,0xb23eb9a8,0xbbd939a8,0xb872b61f,0xbaa73b64,0xbaa73b64,0x3872361f,
0xbb640000,0xb61f3c00,0x3b640000,0x361fbc00,0x361f39a8,0x3b64b9a8,0xb61fb9a8,0xbb6439a8,0x361fbc00,0xbb640000,0xb61f3c00,0x3b640000,0xbb6439a8,0x361f39a8,0x3b64b9a8,0xb61fb9a8,
0xbbd90000,0xb23e3c00,0x323ebc00,0xbbd90000,0x3aa7361f,0x3872bb64,0xb8723b64,0x3aa7361f,0xb872b9a8,0xbaa739a8,0x3aa7b9a8,0xb872b9a8,0x323e3b64,0x3bd9b61f,0xbbd9361f,0x323e3b64,
0xbc000000,0x3c00,0xbc000000,0x3c00,0x3c000000,0xbc00,0x3c000000,0xbc00,0xbc000000,0x3c00,0xbc000000,0x3c00,0x3c000000,0xbc00,0x3c000000,0xbc00,
0xbbd90000,0x323e3c00,0x323e3c00,0x3bd90000,0x3aa7b61f,0xb872bb64,0xb872bb64,0xbaa7361f,0xb87239a8,0x3aa739a8,0x3aa739a8,0x3872b9a8,0x323ebb64,0xbbd9b61f,0xbbd9b61f,0xb23e3b64,
0xbb640000,0x361f3c00,0x3b640000,0xb61fbc00,0x361fb9a8,0xbb64b9a8,0xb61f39a8,0x3b6439a8,0x361f3c00,0x3b640000,0xb61fbc00,0xbb640000,0xbb64b9a8,0xb61f39a8,0x3b6439a8,0x361fb9a8,
0xbaa70000,0x38723c00,0xb872bc00,0xbaa70000,0xb23ebb64,0xbbd9b61f,0x3bd9361f,0xb23ebb64,0x3bd939a8,0x323eb9a8,0xb23e39a8,0x3bd939a8,0xb872361f,0x3aa73b64,0xbaa7bb64,0xb872361f,
0xb9a80000,0x39a83c00,0xb9a80000,0x39a83c00,0xb9a8bc00,0xb9a80000,0xb9a8bc00,0xb9a80000,0x39a80000,0xb9a8bc00,0x39a80000,0xb9a8bc00,0x39a83c00,0x39a80000,0x39a83c00,0x39a80000,
0xb8720000,0x3aa73c00,0x3aa73c00,0x38720000,0xbbd9bb64,0xb23e361f,0xb23e361f,0x3bd93b64,0xb23eb9a8,0xbbd9b9a8,0xbbd9b9a8,0x323e39a8,0x3aa7361f,0xb872bb64,0xb872bb64,0xbaa7b61f,
0xb61f0000,0x3b643c00,0x361f0000,0xbb64bc00,0xbb64b9a8,0x361f39a8,0x3b6439a8,0xb61fb9a8,0xbb64bc00,0xb61f0000,0x3b643c00,0x361f0000,0xb61fb9a8,0xbb64b9a8,0x361f39a8,0x3b6439a8,
0xb23e0000,0x3bd93c00,0xbbd9bc00,0xb23e0000,0xb872b61f,0x3aa73b64,0xbaa7bb64,0xb872b61f,0xbaa7b9a8,0x387239a8,0xb872b9a8,0xbaa7b9a8,0xbbd9bb64,0x323e361f,0xb23eb61f,0xbbd9bb64,
0,0x3c003c00,0,0x3c003c00,0,0x3c003c00,0,0x3c003c00,0,0x3c003c00,0,0x3c003c00,0,0x3c003c00,0,0x3c003c00,
0xb23e0000,0xbbd9bc00,0xbbd9bc00,0x323e0000,0xb872b61f,0xbaa7bb64,0xbaa7bb64,0x3872361f,0xbaa7b9a8,0xb872b9a8,0xb872b9a8,0x3aa739a8,0xbbd9bb64,0xb23eb61f,0xb23eb61f,0x3bd93b64,
0x361f0000,0x3b643c00,0xb61f0000,0xbb64bc00,0x3b6439a8,0x361f39a8,0xbb64b9a8,0xb61fb9a8,0x3b643c00,0xb61f0000,0xbb64bc00,0x361f0000,0x361f39a8,0xbb64b9a8,0xb61fb9a8,0x3b6439a8,
0xb8720000,0xbaa7bc00,0x3aa73c00,0xb8720000,0xbbd9bb64,0x323eb61f,0xb23e361f,0xbbd9bb64,0xb23eb9a8,0x3bd939a8,0xbbd9b9a8,0xb23eb9a8,0x3aa7361f,0x38723b64,0xb872bb64,0x3aa7361f,
0x39a80000,0x39a83c00,0x39a80000,0x39a83c00,0x39a83c00,0xb9a80000,0x39a83c00,0xb9a80000,0xb9a80000,0xb9a8bc00,0xb9a80000,0xb9a8bc00,0xb9a8bc00,0x39a80000,0xb9a8bc00,0x39a80000,
0xbaa70000,0xb872bc00,0xb872bc00,0x3aa70000,0xb23ebb64,0x3bd9361f,0x3bd9361f,0x323e3b64,0x3bd939a8,0xb23e39a8,0xb23e39a8,0xbbd9b9a8,0xb872361f,0xbaa7bb64,0xbaa7bb64,0x3872b61f,
0x3b640000,0x361f3c00,0xbb640000,0xb61fbc00,0xb61f39a8,0xbb64b9a8,0x361fb9a8,0x3b6439a8,0xb61fbc00,0x3b640000,0x361f3c00,0xbb640000,0x3b6439a8,0xb61f39a8,0xbb64b9a8,0x361fb9a8,
0xbbd90000,0xb23ebc00,0x323e3c00,0xbbd90000,0x3aa7b61f,0x38723b64,0xb872bb64,0x3aa7b61f,0xb87239a8,0xbaa7b9a8,0x3aa739a8,0xb87239a8,0x323ebb64,0x3bd9361f,0xbbd9b61f,0x323ebb64,
0x3c000000,0x3c00,0x3c000000,0x3c00,0xbc000000,0xbc00,0xbc000000,0xbc00,0x3c000000,0x3c00,0x3c000000,0x3c00,0xbc000000,0xbc00,0xbc000000,0xbc00,
0xbbd90000,0x323ebc00,0x323ebc00,0x3bd90000,0x3aa7361f,0xb8723b64,0xb8723b64,0xbaa7b61f,0xb872b9a8,0x3aa7b9a8,0x3aa7b9a8,0x387239a8,0x323e3b64,0xbbd9361f,0xbbd9361f,0xb23ebb64,
0x3b640000,0xb61f3c00,0xbb640000,0x361fbc00,0xb61fb9a8,0x3b64b9a8,0x361f39a8,0xbb6439a8,0xb61f3c00,0xbb640000,0x361fbc00,0x3b640000,0x3b64b9a8,0x361f39a8,0xbb6439a8,0xb61fb9a8,
0xbaa70000,0x3872bc00,0xb8723c00,0xbaa70000,0xb23e3b64,0xbbd9361f,0x3bd9b61f,0xb23e3b64,0x3bd9b9a8,0x323e39a8,0xb23eb9a8,0x3bd9b9a8,0xb872b61f,0x3aa7bb64,0xbaa73b64,0xb872b61f,
0x39a80000,0xb9a83c00,0x39a80000,0xb9a83c00,0x39a8bc00,0x39a80000,0x39a8bc00,0x39a80000,0xb9a80000,0x39a8bc00,0xb9a80000,0x39a8bc00,0xb9a83c00,0xb9a80000,0xb9a83c00,0xb9a80000,
0xb8720000,0x3aa7bc00,0x3aa7bc00,0x38720000,0xbbd93b64,0xb23eb61f,0xb23eb61f,0x3bd9bb64,0xb23e39a8,0xbbd939a8,0xbbd939a8,0x323eb9a8,0x3aa7b61f,0xb8723b64,0xb8723b64,0xbaa7361f,
0x361f0000,0xbb643c00,0xb61f0000,0x3b64bc00,0x3b64b9a8,0xb61f39a8,0xbb6439a8,0x361fb9a8,0x3b64bc00,0x361f0000,0xbb643c00,0xb61f0000,0x361fb9a8,0x3b64b9a8,0xb61f39a8,0xbb6439a8,
0xb23e0000,0x3bd9bc00,0xbbd93c00,0xb23e0000,0xb872361f,0x3aa7bb64,0xbaa73b64,0xb872361f,0xbaa739a8,0x3872b9a8,0xb87239a8,0xbaa739a8,0xbbd93b64,0x323eb61f,0xb23e361f,0xbbd93b64,
0,0xbc003c00,0,0xbc003c00,0,0xbc003c00,0,0xbc003c00,0,0xbc003c00,0,0xbc003c00,0,0xbc003c00,0,0xbc003c00,
0x323e0000,0x3bd9bc00,0x3bd9bc00,0xb23e0000,0x3872b61f,0x3aa7bb64,0x3aa7bb64,0xb872361f,0x3aa7b9a8,0x3872b9a8,0x3872b9a8,0xbaa739a8,0x3bd9bb64,0x323eb61f,0x323eb61f,0xbbd93b64,
0xb61f0000,0xbb643c00,0x361f0000,0x3b64bc00,0xbb6439a8,0xb61f39a8,0x3b64b9a8,0x361fb9a8,0xbb643c00,0x361f0000,0x3b64bc00,0xb61f0000,0xb61f39a8,0x3b64b9a8,0x361fb9a8,0xbb6439a8,
0x38720000,0x3aa7bc00,0xbaa73c00,0x38720000,0x3bd9bb64,0xb23eb61f,0x323e361f,0x3bd9bb64,0x323eb9a8,0xbbd939a8,0x3bd9b9a8,0x323eb9a8,0xbaa7361f,0xb8723b64,0x3872bb64,0xbaa7361f,
0xb9a80000,0xb9a83c00,0xb9a80000,0xb9a83c00,0xb9a83c00,0x39a80000,0xb9a83c00,0x39a80000,0x39a80000,0x39a8bc00,0x39a80000,0x39a8bc00,0x39a8bc00,0xb9a80000,0x39a8bc00,0xb9a80000,
0x3aa70000,0x3872bc00,0x3872bc00,0xbaa70000,0x323ebb64,0xbbd9361f,0xbbd9361f,0xb23e3b64,0xbbd939a8,0x323e39a8,0x323e39a8,0x3bd9b9a8,0x3872361f,0x3aa7bb64,0x3aa7bb64,0xb872b61f,
0xbb640000,0xb61f3c00,0x3b640000,0x361fbc00,0x361f39a8,0x3b64b9a8,0xb61fb9a8,0xbb6439a8,0x361fbc00,0xbb640000,0xb61f3c00,0x3b640000,0xbb6439a8,0x361f39a8,0x3b64b9a8,0xb61fb9a8,
0x3bd90000,0x323ebc00,0xb23e3c00,0x3bd90000,0xbaa7b61f,0xb8723b64,0x3872bb64,0xbaa7b61f,0x387239a8,0x3aa7b9a8,0xbaa739a8,0x387239a8,0xb23ebb64,0xbbd9361f,0x3bd9b61f,0xb23ebb64,
0xbc000000,0x3c00,0xbc000000,0x3c00,0x3c000000,0xbc00,0x3c000000,0xbc00,0xbc000000,0x3c00,0xbc000000,0x3c00,0x3c000000,0xbc00,0x3c000000,0xbc00,
0x3bd90000,0xb23ebc00,0xb23ebc00,0xbbd90000,0xbaa7361f,0x38723b64,0x38723b64,0x3aa7b61f,0x3872b9a8,0xbaa7b9a8,0xbaa7b9a8,0xb87239a8,0xb23e3b64,0x3bd9361f,0x3bd9361f,0x323ebb64,
0xbb640000,0x361f3c00,0x3b640000,0xb61fbc00,0x361fb9a8,0xbb64b9a8,0xb61f39a8,0x3b6439a8,0x361f3c00,0x3b640000,0xb61fbc00,0xbb640000,0xbb64b9a8,0xb61f39a8,0x3b6439a8,0x361fb9a8,
0x3aa70000,0xb872bc00,0x38723c00,0x3aa70000,0x323e3b64,0x3bd9361f,0xbbd9b61f,0x323e3b64,0xbbd9b9a8,0xb23e39a8,0x323eb9a8,0xbbd9b9a8,0x3872b61f,0xbaa7bb64,0x3aa73b64,0x3872b61f,
0xb9a80000,0x39a83c00,0xb9a80000,0x39a83c00,0xb9a8bc00,0xb9a80000,0xb9a8bc00,0xb9a80000,0x39a80000,0xb9a8bc00,0x39a80000,0xb9a8bc00,0x39a83c00,0x39a80000,0x39a83c00,0x39a80000,
0x38720000,0xbaa7bc00,0xbaa7bc00,0xb8720000,0x3bd93b64,0x323eb61f,0x323eb61f,0xbbd9bb64,0x323e39a8,0x3bd939a8,0x3bd939a8,0xb23eb9a8,0xbaa7b61f,0x38723b64,0x38723b64,0x3aa7361f,
0xb61f0000,0x3b643c00,0x361f0000,0xbb64bc00,0xbb64b9a8,0x361f39a8,0x3b6439a8,0xb61fb9a8,0xbb64bc00,0xb61f0000,0x3b643c00,0x361f0000,0xb61fb9a8,0xbb64b9a8,0x361f39a8,0x3b6439a8,
0x323e0000,0xbbd9bc00,0x3bd93c00,0x323e0000,0x3872361f,0xbaa7bb64,0x3aa73b64,0x3872361f,0x3aa739a8,0xb872b9a8,0x387239a8,0x3aa739a8,0x3bd93b64,0xb23eb61f,0x323e361f,0x3bd93b64,
0x38003800,0x3800b800,0x38003800,0x3800b800,0x38003800,0x3800b800,0x38003800,0x3800b800,0x38003800,0x3800b800,0x38003800,0x3800b800,0x38003800,0x3800b800,0x38003800,0x3800b800,
0xb8003800,0x38003800,0x39a8,0x39a80000,0xb64938b4,0x38b43649,0x306a398c,0x398cb06a,0xb454393a,0x393a3454,0x3454393a,0x393ab454,0xb06a398c,0x398c306a,0x364938b4,0x38b4b649,
0x38003800,0x3800b800,0x3800b800,0xb800b800,0x393a3454,0x3454b93a,0x3454b93a,0xb93ab454,0x39a80000,0xb9a8,0xb9a8,0xb9a80000,0x393ab454,0xb454b93a,0xb454b93a,0xb93a3454,
0xb8003800,0x38003800,0x39a80000,0xb9a8,0xb06a398c,0x398c306a,0x38b4b649,0xb649b8b4,0x3454393a,0x393ab454,0x3454b93a,0xb93ab454,0x38b43649,0x3649b8b4,0xb06ab98c,0xb98c306a,
0x38003800,0x3800b800,0xb800b800,0xb8003800,0x39a80000,0xb9a8,0xb9a80000,0x39a8,0x3800b800,0xb800b800,0xb8003800,0x38003800,0xb9a8,0xb9a80000,0x39a8,0x39a80000,
0xb8003800,0x38003800,0xb9a8,0xb9a80000,0x306a398c,0x398cb06a,0xb8b4b649,0xb64938b4,0x393a3454,0x3454b93a,0xb93a3454,0x3454393a,0x38b4b649,0xb649b8b4,0xb06a398c,0x398c306a,
0x38003800,0x3800b800,0xb8003800,0x38003800,0x393ab454,0xb454b93a,0x3454393a,0x393ab454,0xb9a8,0xb9a80000,0x39a80000,0xb9a8,0xb93ab454,0xb454393a,0x3454b93a,0xb93ab454,
0xb8003800,0x38003800,0xb9a80000,0x39a8,0x364938b4,0x38b4b649,0xb06a398c,0x398c306a,0x393ab454,0xb454b93a,0x393a3454,0x3454b93a,0xb06ab98c,0xb98c306a,0x3649b8b4,0xb8b4b649,
0x38003800,0x3800b800,0x38003800,0x3800b800,0x3800b800,0xb800b800,0x3800b800,0xb800b800,0xb800b800,0xb8003800,0xb800b800,0xb8003800,0xb8003800,0x38003800,0xb8003800,0x38003800,
0xb8003800,0x38003800,0x39a8,0x39a80000,0x38b43649,0x3649b8b4,0x398cb06a,0xb06ab98c,0x3454b93a,0xb93ab454,0xb454b93a,0xb93a3454,0xb98cb06a,0xb06a398c,0xb8b43649,0x364938b4,
0x38003800,0x3800b800,0x3800b800,0xb800b800,0x3454b93a,0xb93ab454,0xb93ab454,0xb454393a,0xb9a80000,0x39a8,0x39a8,0x39a80000,0x3454393a,0x393ab454,0x393ab454,0xb454b93a,
0xb8003800,0x38003800,0x39a80000,0xb9a8,0x398c306a,0x306ab98c,0xb649b8b4,0xb8b43649,0xb454b93a,0xb93a3454,0xb454393a,0x393a3454,0xb64938b4,0x38b43649,0x398cb06a,0xb06ab98c,
0x38003800,0x3800b800,0xb800b800,0xb8003800,0xb9a8,0xb9a80000,0x39a8,0x39a80000,0xb8003800,0x38003800,0x3800b800,0xb800b800,0x39a80000,0xb9a8,0xb9a80000,0x39a8,
0xb8003800,0x38003800,0xb9a8,0xb9a80000,0x398cb06a,0xb06ab98c,0xb64938b4,0x38b43649,0xb93ab454,0xb454393a,0x393ab454,0xb454b93a,0x364938b4,0x38b4b649,0xb98cb06a,0xb06a398c,
0x38003800,0x3800b800,0xb8003800,0x38003800,0xb454b93a,0xb93a3454,0x393ab454,0xb454b93a,0x39a8,0x39a80000,0xb9a80000,0x39a8,0x3454b93a,0xb93ab454,0x393a3454,0x3454b93a,
0xb8003800,0x38003800,0xb9a80000,0x39a8,0x38b4b649,0xb649b8b4,0x398c306a,0x306ab98c,0xb93a3454,0x3454393a,0xb93ab454,0xb454393a,0x398cb06a,0xb06ab98c,0x38b43649,0x3649b8b4,
0x38003800,0x3800b800,0x38003800,0x3800b800,0xb800b800,0xb8003800,0xb800b800,0xb8003800,0x38003800,0x3800b800,0x38003800,0x3800b800,0xb800b800,0xb8003800,0xb800b800,0xb8003800,
0xb8003800,0x38003800,0x39a8,0x39a80000,0x3649b8b4,0xb8b4b649,0xb06ab98c,0xb98c306a,0xb454393a,0x393a3454,0x3454393a,0x393ab454,0x306ab98c,0xb98cb06a,0xb649b8b4,0xb8b43649,
0x38003800,0x3800b800,0x3800b800,0xb800b800,0xb93ab454,0xb454393a,0xb454393a,0x393a3454,0x39a80000,0xb9a8,0xb9a8,0xb9a80000,0xb93a3454,0x3454393a,0x3454393a,0x393ab454,
0xb8003800,0x38003800,0x39a80000,0xb9a8,0x306ab98c,0xb98cb06a,0xb8b43649,0x364938b4,0x3454393a,0x393ab454,0x3454b93a,0xb93ab454,0xb8b4b649,0xb64938b4,0x306a398c,0x398cb06a,
0x38003800,0x3800b800,0xb800b800,0xb8003800,0xb9a80000,0x39a8,0x39a80000,0xb9a8,0x3800b800,0xb800b800,0xb8003800,0x38003800,0x39a8,0x39a80000,0xb9a8,0xb9a80000,
0xb8003800,0x38003800,0xb9a8,0xb9a80000,0xb06ab98c,0xb98c306a,0x38b43649,0x3649b8b4,0x393a3454,0x3454b93a,0xb93a3454,0x3454393a,0xb8b43649,0x364938b4,0x306ab98c,0xb98cb06a,
0x38003800,0x3800b800,0xb8003800,0x38003800,0xb93a3454,0x3454393a,0xb454b93a,0xb93a3454,0xb9a8,0xb9a80000,0x39a80000,0xb9a8,0x393a3454,0x3454b93a,0xb454393a,0x393a3454,
0xb8003800,0x38003800,0xb9a80000,0x39a8,0xb649b8b4,0xb8b43649,0x306ab98c,0xb98cb06a,0x393ab454,0xb454b93a,0x393a3454,0x3454b93a,0x306a398c,0x398cb06a,0xb64938b4,0x38b43649,
0x38003800,0x3800b800,0x38003800,0x3800b800,0xb8003800,0x38003800,0xb8003800,0x38003800,0xb800b800,0xb8003800,0xb800b800,0xb8003800,0x3800b800,0xb800b800,0x3800b800,0xb800b800,
0xb8003800,0x38003800,0x39a8,0x39a80000,0xb8b4b649,0xb64938b4,0xb98c306a,0x306a398c,0x3454b93a,0xb93ab454,0xb454b93a,0xb93a3454,0x398c306a,0x306ab98c,0x38b4b649,0xb649b8b4,
0x38003800,0x3800b800,0x3800b800,0xb800b800,0xb454393a,0x393a3454,0x393a3454,0x3454b93a,0xb9a80000,0x39a8,0x39a8,0x39a80000,0xb454b93a,0xb93a3454,0xb93a3454,0x3454393a,
0xb8003800,0x38003800,0x39a80000,0xb9a8,0xb98cb06a,0xb06a398c,0x364938b4,0x38b4b649,0xb454b93a,0xb93a3454,0xb454393a,0x393a3454,0x3649b8b4,0xb8b4b649,0xb98c306a,0x306a398c,
0x38003800,0x3800b800,0xb800b800,0xb8003800,0x39a8,0x39a80000,0xb9a8,0xb9a80000,0xb8003800,0x38003800,0x3800b800,0xb800b800,0xb9a80000,0x39a8,0x39a80000,0xb9a8,
0xb8003800,0x38003800,0xb9a8,0xb9a80000,0xb98c306a,0x306a398c,0x3649b8b4,0xb8b4b649,0xb93ab454,0xb454393a,0x393ab454,0xb454b93a,0xb649b8b4,0xb8b43649,0x398c306a,0x306ab98c,
0x38003800,0x3800b800,0xb8003800,0x38003800,0x3454393a,0x393ab454,0xb93a3454,0x3454393a,0x39a8,0x39a80000,0xb9a80000,0x39a8,0xb454393a,0x393a3454,0xb93ab454,0xb454393a,
0xb8003800,0x38003800,0xb9a80000,0x39a8,0xb8b43649,0x364938b4,0xb98cb06a,0xb06a398c,0xb93a3454,0x3454393a,0xb93ab454,0xb454393a,0xb98c306a,0x306a398c,0xb8b4b649,0xb64938b4,
0x38003800,0x3800b800,0x38003800,0x3800b800,0x38003800,0x3800b800,0x38003800,0x3800b800,0x38003800,0x3800b800,0x38003800,0x3800b800,0x38003800,0x3800b800,0x38003800,0x3800b800,
0x38003800,0x3800b800,0x39a80000,0xb9a8,0x38b43649,0x3649b8b4,0x398cb06a,0xb06ab98c,0x393a3454,0x3454b93a,0x393ab454,0xb454b93a,0x398c306a,0x306ab98c,0x38b4b649,0xb649b8b4,
0xb800b800,0xb8003800,0xb8003800,0x38003800,0xb93ab454,0xb454393a,0xb454393a,0x393a3454,0xb9a80000,0x39a8,0x39a8,0x39a80000,0xb93a3454,0x3454393a,0x3454393a,0x393ab454,
0xb800b800,0xb8003800,0x39a8,0x39a80000,0xb98cb06a,0xb06a398c,0x364938b4,0x38b4b649,0xb93a3454,0x3454393a,0x393a3454,0x3454b93a,0xb64938b4,0x38b43649,0x398cb06a,0xb06ab98c,
0x38003800,0x3800b800,0xb800b800,0xb8003800,0x39a80000,0xb9a8,0xb9a80000,0x39a8,0x3800b800,0xb800b800,0xb8003800,0x38003800,0xb9a8,0xb9a80000,0x39a8,0x39a80000,
0x38003800,0x3800b800,0xb9a80000,0x39a8,0x398cb06a,0xb06ab98c,0xb64938b4,0x38b43649,0x3454b93a,0xb93ab454,0x3454393a,0x393ab454,0xb649b8b4,0xb8b43649,0x398c306a,0x306ab98c,
0xb800b800,0xb8003800,0x3800b800,0xb800b800,0xb93a3454,0x3454393a,0xb454b93a,0xb93a3454,0x39a8,0x39a80000,0xb9a80000,0x39a8,0x393a3454,0x3454b93a,0xb454393a,0x393a3454,
0xb800b800,0xb8003800,0xb9a8,0xb9a80000,0xb8b43649,0x364938b4,0xb98cb06a,0xb06a398c,0x3454393a,0x393ab454,0xb454393a,0x393a3454,0x398cb06a,0xb06ab98c,0x38b43649,0x3649b8b4,
0x38003800,0x3800b800,0x38003800,0x3800b800,0x3800b800,0xb800b800,0x3800b800,0xb800b800,0xb800b800,0xb8003800,0xb800b800,0xb8003800,0xb8003800,0x38003800,0xb8003800,0x38003800,
0x38003800,0x3800b800,0x39a80000,0xb9a8,0x3649b8b4,0xb8b4b649,0xb06ab98c,0xb98c306a,0xb93ab454,0xb454393a,0xb93a3454,0x3454393a,0xb06a398c,0x398c306a,0x364938b4,0x38b4b649,
0xb800b800,0xb8003800,0xb8003800,0x38003800,0xb454393a,0x393a3454,0x393a3454,0x3454b93a,0x39a80000,0xb9a8,0xb9a8,0xb9a80000,0xb454b93a,0xb93a3454,0xb93a3454,0x3454393a,
0xb800b800,0xb8003800,0x39a8,0x39a80000,0xb06a398c,0x398c306a,0x38b4b649,0xb649b8b4,0x393ab454,0xb454b93a,0xb93ab454,0xb454393a,0xb8b4b649,0xb64938b4,0x306a398c,0x398cb06a,
0x38003800,0x3800b800,0xb800b800,0xb8003800,0xb9a8,0xb9a80000,0x39a8,0x39a80000,0xb8003800,0x38003800,0x3800b800,0xb800b800,0x39a80000,0xb9a8,0xb9a80000,0x39a8,
0x38003800,0x3800b800,0xb9a80000,0x39a8,0xb06ab98c,0xb98c306a,0x38b43649,0x3649b8b4,0xb454393a,0x393a3454,0xb454b93a,0xb93a3454,0x38b4b649,0xb649b8b4,0xb06a398c,0x398c306a,
0xb800b800,0xb8003800,0x3800b800,0xb800b800,0x3454393a,0x393ab454,0xb93a3454,0x3454393a,0xb9a8,0xb9a80000,0x39a80000,0xb9a8,0xb454393a,0x393a3454,0xb93ab454,0xb454393a,
0xb800b800,0xb8003800,0xb9a8,0xb9a80000,0x364938b4,0x38b4b649,0xb06a398c,0x398c306a,0xb454b93a,0xb93a3454,0x3454b93a,0xb93ab454,0x306a398c,0x398cb06a,0xb64938b4,0x38b43649,
0x38003800,0x3800b800,0x38003800,0x3800b800,0xb800b800,0xb8003800,0xb800b800,0xb8003800,0x38003800,0x3800b800,0x38003800,0x3800b800,0xb800b800,0xb8003800,0xb800b800,0xb8003800,
0x38003800,0x3800b800,0x39a80000,0xb9a8,0xb8b4b649,0xb64938b4,0xb98c306a,0x306a398c,0x393a3454,0x3454b93a,0x393ab454,0xb454b93a,0xb98cb06a,0xb06a398c,0xb8b43649,0x364938b4,
0xb800b800,0xb8003800,0xb8003800,0x38003800,0x393a3454,0x3454b93a,0x3454b93a,0xb93ab454,0xb9a80000,0x39a8,0x39a8,0x39a80000,0x393ab454,0xb454b93a,0xb454b93a,0xb93a3454,
0xb800b800,0xb8003800,0x39a8,0x39a80000,0x398c306a,0x306ab98c,0xb649b8b4,0xb8b43649,0xb93a3454,0x3454393a,0x393a3454,0x3454b93a,0x3649b8b4,0xb8b4b649,0xb98c306a,0x306a398c,
0x38003800,0x3800b800,0xb800b800,0xb8003800,0xb9a80000,0x39a8,0x39a80000,0xb9a8,0x3800b800,0xb800b800,0xb8003800,0x38003800,0x39a8,0x39a80000,0xb9a8,0xb9a80000,
0x38003800,0x3800b800,0xb9a80000,0x39a8,0xb98c306a,0x306a398c,0x3649b8b4,0xb8b4b649,0x3454b93a,0xb93ab454,0x3454393a,0x393ab454,0x364938b4,0x38b4b649,0xb98cb06a,0xb06a398c,
0xb800b800,0xb8003800,0x3800b800,0xb800b800,0x393ab454,0xb454b93a,0x3454393a,0x393ab454,0x39a8,0x39a80000,0xb9a80000,0x39a8,0xb93ab454,0xb454393a,0x3454b93a,0xb93ab454,
0xb800b800,0xb8003800,0xb9a8,0xb9a80000,0x38b4b649,0xb649b8b4,0x398c306a,0x306ab98c,0x3454393a,0x393ab454,0xb454393a,0x393a3454,0xb98c306a,0x306a398c,0xb8b4b649,0xb64938b4,
0x38003800,0x3800b800,0x38003800,0x3800b800,0xb8003800,0x38003800,0xb8003800,0x38003800,0xb800b800,0xb8003800,0xb800b800,0xb8003800,0x3800b800,0xb800b800,0x3800b800,0xb800b800,
0x38003800,0x3800b800,0x39a80000,0xb9a8,0xb64938b4,0x38b43649,0x306a398c,0x398cb06a,0xb93ab454,0xb454393a,0xb93a3454,0x3454393a,0x306ab98c,0xb98cb06a,0xb649b8b4,0xb8b43649,
0xb800b800,0xb8003800,0xb8003800,0x38003800,0x3454b93a,0xb93ab454,0xb93ab454,0xb454393a,0x39a80000,0xb9a8,0xb9a8,0xb9a80000,0x3454393a,0x393ab454,0x393ab454,0xb454b93a,
0xb800b800,0xb8003800,0x39a8,0x39a80000,0x306ab98c,0xb98cb06a,0xb8b43649,0x364938b4,0x393ab454,0xb454b93a,0xb93ab454,0xb454393a,0x38b43649,0x3649b8b4,0xb06ab98c,0xb98c306a,
0x38003800,0x3800b800,0xb800b800,0xb8003800,0x39a8,0x39a80000,0xb9a8,0xb9a80000,0xb8003800,0x38003800,0x3800b800,0xb800b800,0xb9a80000,0x39a8,0x39a80000,0xb9a8,
0x38003800,0x3800b800,0xb9a80000,0x39a8,0x306a398c,0x398cb06a,0xb8b4b649,0xb64938b4,0xb454393a,0x393a3454,0xb454b93a,0xb93a3454,0xb8b43649,0x364938b4,0x306ab98c,0xb98cb06a,
0xb800b800,0xb8003800,0x3800b800,0xb800b800,0xb454b93a,0xb93a3454,0x393ab454,0xb454b93a,0xb9a8,0xb9a80000,0x39a80000,0xb9a8,0x3454b93a,0xb93ab454,0x393a3454,0x3454b93a,
0xb800b800,0xb8003800,0xb9a8,0xb9a80000,0xb649b8b4,0xb8b43649,0x306ab98c,0xb98cb06a,0xb454b93a,0xb93a3454,0x3454b93a,0xb93ab454,0xb06ab98c,0xb98c306a,0x3649b8b4,0xb8b4b649,
0x38003800,0xb8003800,0x38003800,0xb8003800,0x38003800,0xb8003800,0x38003800,0xb8003800,0x38003800,0xb8003800,0x38003800,0xb8003800,0x38003800,0xb8003800,0x38003800,0xb8003800,
0xb8003800,0xb800b800,0xb9a80000,0xb9a8,0xb8b43649,0xb649b8b4,0xb98cb06a,0x306ab98c,0xb93a3454,0xb454b93a,0xb93ab454,0x3454b93a,0xb98c306a,0xb06ab98c,0xb8b4b649,0x3649b8b4,
0x38003800,0xb8003800,0xb8003800,0xb800b800,0x3454393a,0xb93a3454,0xb93a3454,0xb454b93a,0x39a8,0xb9a80000,0xb9a80000,0xb9a8,0xb454393a,0xb93ab454,0xb93ab454,0x3454b93a,
0xb8003800,0xb800b800,0xb9a8,0x39a80000,0xb98c306a,0xb06ab98c,0x3649b8b4,0x38b43649,0xb93ab454,0x3454b93a,0x393ab454,0x3454393a,0xb649b8b4,0x38b4b649,0x398c306a,0xb06a398c,
0x38003800,0xb8003800,0xb800b800,0x3800b800,0x39a8,0xb9a80000,0xb9a8,0x39a80000,0xb8003800,0xb800b800,0x3800b800,0x38003800,0xb9a80000,0xb9a8,0x39a80000,0x39a8,
0xb8003800,0xb800b800,0x39a80000,0x39a8,0xb98cb06a,0x306ab98c,0x364938b4,0xb8b43649,0xb454b93a,0x393ab454,0xb454393a,0xb93ab454,0x3649b8b4,0x38b43649,0xb98c306a,0xb06ab98c,
0x38003800,0xb8003800,0x3800b800,0x38003800,0xb454393a,0xb93ab454,0x393a3454,0xb454393a,0xb9a80000,0xb9a8,0x39a8,0xb9a80000,0xb454b93a,0x393ab454,0xb93a3454,0xb454b93a,
0xb8003800,0xb800b800,0x39a8,0xb9a80000,0xb8b4b649,0x3649b8b4,0xb98c306a,0xb06ab98c,0x3454b93a,0x393a3454,0xb454b93a,0x393ab454,0x398c306a,0xb06a398c,0x38b4b649,0x364938b4,
0x38003800,0xb8003800,0x38003800,0xb8003800,0xb8003800,0xb800b800,0xb8003800,0xb800b800,0xb800b800,0x3800b800,0xb800b800,0x3800b800,0x3800b800,0x38003800,0x3800b800,0x38003800,
0xb8003800,0xb800b800,0xb9a80000,0xb9a8,0xb649b8b4,0x38b4b649,0x306ab98c,0x398c306a,0x393ab454,0x3454393a,0x393a3454,0xb454393a,0x306a398c,0xb98c306a,0xb64938b4,0xb8b4b649,
0x38003800,0xb8003800,0xb8003800,0xb800b800,0xb93a3454,0xb454b93a,0xb454b93a,0x393ab454,0xb9a8,0x39a80000,0x39a80000,0x39a8,0x393a3454,0xb454393a,0xb454393a,0xb93ab454,
0xb8003800,0xb800b800,0xb9a8,0x39a80000,0xb06ab98c,0x398cb06a,0x38b43649,0xb64938b4,0x393a3454,0xb454393a,0xb93a3454,0xb454b93a,0xb8b43649,0xb649b8b4,0x306ab98c,0x398c306a,
0x38003800,0xb8003800,0xb800b800,0x3800b800,0xb9a80000,0xb9a8,0x39a80000,0x39a8,0x3800b800,0x38003800,0xb8003800,0xb800b800,0x39a8,0xb9a80000,0xb9a8,0x39a80000,
0xb8003800,0xb800b800,0x39a80000,0x39a8,0x306ab98c,0x398c306a,0xb8b43649,0xb649b8b4,0x3454393a,0xb93a3454,0x3454b93a,0x393a3454,0xb8b4b649,0x3649b8b4,0x306a398c,0xb98c306a,
0x38003800,0xb8003800,0x3800b800,0x38003800,0xb93ab454,0x3454b93a,0xb454393a,0xb93ab454,0x39a80000,0x39a8,0xb9a8,0x39a80000,0xb93a3454,0xb454b93a,0x3454393a,0xb93a3454,
0xb8003800,0xb800b800,0x39a8,0xb9a80000,0x3649b8b4,0x38b43649,0xb06ab98c,0x398cb06a,0xb454393a,0xb93ab454,0x3454393a,0xb93a3454,0x306ab98c,0x398c306a,0xb649b8b4,0x38b4b649,
0x38003800,0xb8003800,0x38003800,0xb8003800,0xb800b800,0x3800b800,0xb800b800,0x3800b800,0x38003800,0xb8003800,0x38003800,0xb8003800,0xb800b800,0x3800b800,0xb800b800,0x3800b800,
0xb8003800,0xb800b800,0xb9a80000,0xb9a8,0x38b4b649,0x364938b4,0x398c306a,0xb06a398c,0xb93a3454,0xb454b93a,0xb93ab454,0x3454b93a,0x398cb06a,0x306a398c,0x38b43649,0xb64938b4,
0x38003800,0xb8003800,0xb8003800,0xb800b800,0xb454b93a,0x393ab454,0x393ab454,0x3454393a,0x39a8,0xb9a80000,0xb9a80000,0xb9a8,0x3454b93a,0x393a3454,0x393a3454,0xb454393a,
0xb8003800,0xb800b800,0xb9a8,0x39a80000,0x398cb06a,0x306a398c,0xb64938b4,0xb8b4b649,0xb93ab454,0x3454b93a,0x393ab454,0x3454393a,0x364938b4,0xb8b43649,0xb98cb06a,0x306ab98c,
0x38003800,0xb8003800,0xb800b800,0x3800b800,0xb9a8,0x39a80000,0x39a8,0xb9a80000,0xb8003800,0xb800b800,0x3800b800,0x38003800,0x39a80000,0x39a8,0xb9a80000,0xb9a8,
0xb8003800,0xb800b800,0x39a80000,0x39a8,0x398c306a,0xb06a398c,0xb649b8b4,0x38b4b649,0xb454b93a,0x393ab454,0xb454393a,0xb93ab454,0xb64938b4,0xb8b4b649,0x398cb06a,0x306a398c,
0x38003800,0xb8003800,0x3800b800,0x38003800,0x3454b93a,0x393a3454,0xb93ab454,0x3454b93a,0xb9a80000,0xb9a8,0x39a8,0xb9a80000,0x3454393a,0xb93a3454,0x393ab454,0x3454393a,
0xb8003800,0xb800b800,0x39a8,0xb9a80000,0x38b43649,0xb64938b4,0x398cb06a,0x306a398c,0x3454b93a,0x393a3454,0xb454b93a,0x393ab454,0xb98cb06a,0x306ab98c,0xb8b43649,0xb649b8b4,
0x38003800,0xb8003800,0x38003800,0xb8003800,0x3800b800,0x38003800,0x3800b800,0x38003800,0xb800b800,0x3800b800,0xb800b800,0x3800b800,0xb8003800,0xb800b800,0xb8003800,0xb800b800,
0xb8003800,0xb800b800,0xb9a80000,0xb9a8,0x364938b4,0xb8b43649,0xb06a398c,0xb98cb06a,0x393ab454,0x3454393a,0x393a3454,0xb454393a,0xb06ab98c,0x398cb06a,0x3649b8b4,0x38b43649,
0x38003800,0xb8003800,0xb8003800,0xb800b800,0x393ab454,0x3454393a,0x3454393a,0xb93a3454,0xb9a8,0x39a80000,0x39a80000,0x39a8,0xb93ab454,0x3454b93a,0x3454b93a,0x393a3454,
0xb8003800,0xb800b800,0xb9a8,0x39a80000,0x306a398c,0xb98c306a,0xb8b4b649,0x3649b8b4,0x393a3454,0xb454393a,0xb93a3454,0xb454b93a,0x38b4b649,0x364938b4,0xb06a398c,0xb98cb06a,
0x38003800,0xb8003800,0xb800b800,0x3800b800,0x39a80000,0x39a8,0xb9a80000,0xb9a8,0x3800b800,0x38003800,0xb8003800,0xb800b800,0xb9a8,0x39a80000,0x39a8,0xb9a80000,
0xb8003800,0xb800b800,0x39a80000,0x39a8,0xb06a398c,0xb98cb06a,0x38b4b649,0x364938b4,0x3454393a,0xb93a3454,0x3454b93a,0x393a3454,0x38b43649,0xb64938b4,0xb06ab98c,0x398cb06a,
0x38003800,0xb8003800,0x3800b800,0x38003800,0x393a3454,0xb454393a,0x3454b93a,0x393a3454,0x39a80000,0x39a8,0xb9a8,0x39a80000,0x393ab454,0x3454393a,0xb454b93a,0x393ab454,
0xb8003800,0xb800b800,0x39a8,0xb9a80000,0xb64938b4,0xb8b4b649,0x306a398c,0xb98c306a,0xb454393a,0xb93ab454,0x3454393a,0xb93a3454,0xb06a398c,0xb98cb06a,0x364938b4,0xb8b43649,
0x38003800,0xb8003800,0x38003800,0xb8003800,0x38003800,0xb8003800,0x38003800,0xb8003800,0x38003800,0xb8003800,0x38003800,0xb8003800,0x38003800,0xb8003800,0x38003800,0xb8003800,
0xb800b800,0x3800b800,0xb9a8,0x39a80000,0xb649b8b4,0x38b4b649,0x306ab98c,0x398c306a,0xb454b93a,0x393ab454,0x3454b93a,0x393a3454,0xb06ab98c,0x398cb06a,0x3649b8b4,0x38b43649,
0xb800b800,0x3800b800,0x3800b800,0x38003800,0xb454b93a,0x393ab454,0x393ab454,0x3454393a,0xb9a8,0x39a80000,0x39a80000,0x39a8,0x3454b93a,0x393a3454,0x393a3454,0xb454393a,
0x38003800,0xb8003800,0xb9a80000,0xb9a8,0x306a398c,0xb98c306a,0xb8b4b649,0x3649b8b4,0xb454393a,0xb93ab454,0xb454b93a,0x393ab454,0xb8b43649,0xb649b8b4,0x306ab98c,0x398c306a,
0x38003800,0xb8003800,0xb800b800,0x3800b800,0x39a8,0xb9a80000,0xb9a8,0x39a80000,0xb8003800,0xb800b800,0x3800b800,0x38003800,0xb9a80000,0xb9a8,0x39a80000,0x39a8,
0xb800b800,0x3800b800,0x39a8,0xb9a80000,0x306ab98c,0x398c306a,0xb8b43649,0xb649b8b4,0x393ab454,0x3454393a,0xb93ab454,0x3454b93a,0x38b43649,0xb64938b4,0xb06ab98c,0x398cb06a,
0xb800b800,0x3800b800,0xb8003800,0xb800b800,0x3454b93a,0x393a3454,0xb93ab454,0x3454b93a,0x39a80000,0x39a8,0xb9a8,0x39a80000,0x3454393a,0xb93a3454,0x393ab454,0x3454393a,
0x38003800,0xb8003800,0x39a80000,0x39a8,0xb64938b4,0xb8b4b649,0x306a398c,0xb98c306a,0xb93ab454,0x3454b93a,0xb93a3454,0xb454b93a,0x306ab98c,0x398c306a,0xb649b8b4,0x38b4b649,
0x38003800,0xb8003800,0x38003800,0xb8003800,0xb8003800,0xb800b800,0xb8003800,0xb800b800,0xb800b800,0x3800b800,0xb800b800,0x3800b800,0x3800b800,0x38003800,0x3800b800,0x38003800,
0xb800b800,0x3800b800,0xb9a8,0x39a80000,0x38b4b649,0x364938b4,0x398c306a,0xb06a398c,0x3454393a,0xb93a3454,0xb454393a,0xb93ab454,0xb98c306a,0xb06ab98c,0xb8b4b649,0x3649b8b4,
0xb800b800,0x3800b800,0x3800b800,0x38003800,0x393ab454,0x3454393a,0x3454393a,0xb93a3454,0x39a8,0xb9a80000,0xb9a80000,0xb9a8,0xb93ab454,0x3454b93a,0x3454b93a,0x393a3454,
0x38003800,0xb8003800,0xb9a80000,0xb9a8,0xb98c306a,0xb06ab98c,0x3649b8b4,0x38b43649,0x3454b93a,0x393a3454,0x3454393a,0xb93a3454,0x364938b4,0xb8b43649,0xb98cb06a,0x306ab98c,
0x38003800,0xb8003800,0xb800b800,0x3800b800,0xb9a80000,0xb9a8,0x39a80000,0x39a8,0x3800b800,0x38003800,0xb8003800,0xb800b800,0x39a8,0xb9a80000,0xb9a8,0x39a80000,
0xb800b800,0x3800b800,0x39a8,0xb9a80000,0x398c306a,0xb06a398c,0xb649b8b4,0x38b4b649,0xb93a3454,0xb454b93a,0x393a3454,0xb454393a,0x3649b8b4,0x38b43649,0xb98c306a,0xb06ab98c,
0xb800b800,0x3800b800,0xb8003800,0xb800b800,0x393a3454,0xb454393a,0x3454b93a,0x393a3454,0xb9a80000,0xb9a8,0x39a8,0xb9a80000,0x393ab454,0x3454393a,0xb454b93a,0x393ab454,
0x38003800,0xb8003800,0x39a80000,0x39a8,0xb8b4b649,0x3649b8b4,0xb98c306a,0xb06ab98c,0x393a3454,0xb454393a,0x393ab454,0x3454393a,0xb98cb06a,0x306ab98c,0xb8b43649,0xb649b8b4,
0x38003800,0xb8003800,0x38003800,0xb8003800,0xb800b800,0x3800b800,0xb800b800,0x3800b800,0x38003800,0xb8003800,0x38003800,0xb8003800,0xb800b800,0x3800b800,0xb800b800,0x3800b800,
0xb800b800,0x3800b800,0xb9a8,0x39a80000,0x364938b4,0xb8b43649,0xb06a398c,0xb98cb06a,0xb454b93a,0x393ab454,0x3454b93a,0x393a3454,0x306a398c,0xb98c306a,0xb64938b4,0xb8b4b649,
0xb800b800,0x3800b800,0x3800b800,0x38003800,0x3454393a,0xb93a3454,0xb93a3454,0xb454b93a,0xb9a8,0x39a80000,0x39a80000,0x39a8,0xb454393a,0xb93ab454,0xb93ab454,0x3454b93a,
0x38003800,0xb8003800,0xb9a80000,0xb9a8,0xb06ab98c,0x398cb06a,0x38b43649,0xb64938b4,0xb454393a,0xb93ab454,0xb454b93a,0x393ab454,0x38b4b649,0x364938b4,0xb06a398c,0xb98cb06a,
0x38003800,0xb8003800,0xb800b800,0x3800b800,0xb9a8,0x39a80000,0x39a8,0xb9a80000,0xb8003800,0xb800b800,0x3800b800,0x38003800,0x39a80000,0x39a8,0xb9a80000,0xb9a8,
0xb800b800,0x3800b800,0x39a8,0xb9a80000,0xb06a398c,0xb98cb06a,0x38b4b649,0x364938b4,0x393ab454,0x3454393a,0xb93ab454,0x3454b93a,0xb8b4b649,0x3649b8b4,0x306a398c,0xb98c306a,
0xb800b800,0x3800b800,0xb8003800,0xb800b800,0xb454393a,0xb93ab454,0x393a3454,0xb454393a,0x39a80000,0x39a8,0xb9a8,0x39a80000,0xb454b93a,0x393ab454,0xb93a3454,0xb454b93a,
0x38003800,0xb8003800,0x39a80000,0x39a8,0x3649b8b4,0x38b43649,0xb06ab98c,0x398cb06a,0xb93ab454,0x3454b93a,0xb93a3454,0xb454b93a,0xb06a398c,0xb98cb06a,0x364938b4,0xb8b43649,
0x38003800,0xb8003800,0x38003800,0xb8003800,0x3800b800,0x38003800,0x3800b800,0x38003800,0xb800b800,0x3800b800,0xb800b800,0x3800b800,0xb8003800,0xb800b800,0xb8003800,0xb800b800,
0xb800b800,0x3800b800,0xb9a8,0x39a80000,0xb8b43649,0xb649b8b4,0xb98cb06a,0x306ab98c,0x3454393a,0xb93a3454,0xb454393a,0xb93ab454,0x398cb06a,0x306a398c,0x38b43649,0xb64938b4,
0xb800b800,0x3800b800,0x3800b800,0x38003800,0xb93a3454,0xb454b93a,0xb454b93a,0x393ab454,0x39a8,0xb9a80000,0xb9a80000,0xb9a8,0x393a3454,0xb454393a,0xb454393a,0xb93ab454,
0x38003800,0xb8003800,0xb9a80000,0xb9a8,0x398cb06a,0x306a398c,0xb64938b4,0xb8b4b649,0x3454b93a,0x393a3454,0x3454393a,0xb93a3454,0xb649b8b4,0x38b4b649,0x398c306a,0xb06a398c,
0x38003800,0xb8003800,0xb800b800,0x3800b800,0x39a80000,0x39a8,0xb9a80000,0xb9a8,0x3800b800,0x38003800,0xb8003800,0xb800b800,0xb9a8,0x39a80000,0x39a8,0xb9a80000,
0xb800b800,0x3800b800,0x39a8,0xb9a80000,0xb98cb06a,0x306ab98c,0x364938b4,0xb8b43649,0xb93a3454,0xb454b93a,0x393a3454,0xb454393a,0xb64938b4,0xb8b4b649,0x398cb06a,0x306a398c,
0xb800b800,0x3800b800,0xb8003800,0xb800b800,0xb93ab454,0x3454b93a,0xb454393a,0xb93ab454,0xb9a80000,0xb9a8,0x39a8,0xb9a80000,0xb93a3454,0xb454b93a,0x3454393a,0xb93a3454,
0x38003800,0xb8003800,0x39a80000,0x39a8,0x38b43649,0xb64938b4,0x398cb06a,0x306a398c,0x393a3454,0xb454393a,0x393ab454,0x3454393a,0x398c306a,0xb06a398c,0x38b4b649,0x364938b4,
0x3f803f80,0xbf803f80,0x3f80bf80,0x3f803f80,0x3f803f80,0xbf803f80,0x3f80bf80,0x3f803f80,0x3f803f80,0xbf803f80,0x3f80bf80,0x3f803f80,0x3f803f80,0xbf803f80,0x3f80bf80,0x3f803f80,
0x3f973f80,0xbf493f80,0x3f49bf80,0x3f973f80,0x3fb23f0b,0xbe8d3fa7,0x3e8dbfa7,0x3fb23f0b,0x3fb20000,0x3e8d3fb5,0xbe8dbfb5,0x3fb20000,0x3f97bf0b,0x3f493fa7,0xbf49bfa7,0x3f97bf0b,
0x3fa73f80,0xbf0b3f80,0x3f0bbf80,0x3fa73f80,0x3fa70000,0x3f0b3fb5,0xbf0bbfb5,0x3fa70000,0x3f0bbf80,0x3fa73f80,0xbfa7bf80,0x3f0bbf80,0xbf0bbfb5,0x3fa70000,0xbfa70000,0xbf0bbfb5,
0x3fb23f80,0xbe8d3f80,0x3e8dbf80,0x3fb23f80,0x3f49bf0b,0x3f973fa7,0xbf97bfa7,0x3f49bf0b,0xbf49bfb5,0x3f970000,0xbf970000,0xbf49bfb5,0xbfb2bf0b,0xbe8dbfa7,0x3e8d3fa7,0xbfb2bf0b,
0x3fb53f80,0x3f80,0xbf80,0x3fb53f80,0xbf80,0x3fb53f80,0xbfb5bf80,0xbf80,0xbfb5bf80,0xbf80,0x3f80,0xbfb5bf80,0x3f80,0xbfb5bf80,0x3fb53f80,0x3f80,
0x3fb23f80,0x3e8d3f80,0xbe8dbf80,0x3fb23f80,0xbf49bfa7,0x3f973f0b,0xbf97bf0b,0xbf49bfa7,0xbf490000,0xbf97bfb5,0x3f973fb5,0xbf490000,0x3fb23fa7,0xbe8d3f0b,0x3e8dbf0b,0x3fb23fa7,
0x3fa73f80,0x3f0b3f80,0xbf0bbf80,0x3fa73f80,0xbfa7bfb5,0x3f0b0000,0xbf0b0000,0xbfa7bfb5,0x3f0b3f80,0xbfa7bf80,0x3fa73f80,0x3f0b3f80,0x3f0b0000,0x3fa73fb5,0xbfa7bfb5,0x3f0b0000,
0x3f973f80,0x3f493f80,0xbf49bf80,0x3f973f80,0xbfb2bfa7,0xbe8dbf0b,0x3e8d3f0b,0xbfb2bfa7,0x3fb23fb5,0xbe8d0000,0x3e8d0000,0x3fb23fb5,0xbf97bfa7,0x3f493f0b,0xbf49bf0b,0xbf97bfa7,
0x3f803f80,0x3f803f80,0xbf80bf80,0x3f803f80,0xbf80bf80,0xbf80bf80,0x3f803f80,0xbf80bf80,0x3f803f80,0x3f803f80,0xbf80bf80,0x3f803f80,0xbf80bf80,0xbf80bf80,0x3f803f80,0xbf80bf80,
0x3f493f80,0x3f973f80,0xbf97bf80,0x3f493f80,0xbe8dbf0b,0xbfb2bfa7,0x3fb23fa7,0xbe8dbf0b,0xbe8d0000,0x3fb23fb5,0xbfb2bfb5,0xbe8d0000,0x3f493f0b,0xbf97bfa7,0x3f973fa7,0x3f493f0b,
0x3f0b3f80,0x3fa73f80,0xbfa7bf80,0x3f0b3f80,0x3f0b0000,0xbfa7bfb5,0x3fa73fb5,0x3f0b0000,0xbfa7bf80,0x3f0b3f80,0xbf0bbf80,0xbfa7bf80,0x3fa73fb5,0x3f0b0000,0xbf0b0000,0x3fa73fb5,
0x3e8d3f80,0x3fb23f80,0xbfb2bf80,0x3e8d3f80,0x3f973f0b,0xbf49bfa7,0x3f493fa7,0x3f973f0b,0xbf97bfb5,0xbf490000,0x3f490000,0xbf97bfb5,0xbe8d3f0b,0x3fb23fa7,0xbfb2bfa7,0xbe8d3f0b,
0x3f80,0x3fb53f80,0xbfb5bf80,0x3f80,0x3fb53f80,0xbf80,0x3f80,0x3fb53f80,0xbf80,0xbfb5bf80,0x3fb53f80,0xbf80,0xbfb5bf80,0x3f80,0xbf80,0xbfb5bf80,
0xbe8d3f80,0x3fb23f80,0xbfb2bf80,0xbe8d3f80,0x3f973fa7,0x3f49bf0b,0xbf493f0b,0x3f973fa7,0x3f970000,0xbf49bfb5,0x3f493fb5,0x3f970000,0xbe8dbfa7,0xbfb2bf0b,0x3fb23f0b,0xbe8dbfa7,
0xbf0b3f80,0x3fa73f80,0xbfa7bf80,0xbf0b3f80,0x3f0b3fb5,0x3fa70000,0xbfa70000,0x3f0b3fb5,0x3fa73f80,0x3f0bbf80,0xbf0b3f80,0x3fa73f80,0x3fa70000,0xbf0bbfb5,0x3f0b3fb5,0x3fa70000,
0xbf493f80,0x3f973f80,0xbf97bf80,0xbf493f80,0xbe8d3fa7,0x3fb23f0b,0xbfb2bf0b,0xbe8d3fa7,0x3e8d3fb5,0x3fb20000,0xbfb20000,0x3e8d3fb5,0x3f493fa7,0x3f97bf0b,0xbf973f0b,0x3f493fa7,
0x3f803f80,0xbf803f80,0xbf803f80,0xbf80bf80,0x3f803f80,0xbf803f80,0xbf803f80,0xbf80bf80,0x3f803f80,0xbf803f80,0xbf803f80,0xbf80bf80,0x3f803f80,0xbf803f80,0xbf803f80,0xbf80bf80,
0x3f493f80,0xbf973f80,0xbf973f80,0xbf49bf80,0x3e8d3fa7,0xbfb23f0b,0xbfb23f0b,0xbe8dbfa7,0xbe8d3fb5,0xbfb20000,0xbfb20000,0x3e8dbfb5,0xbf493fa7,0xbf97bf0b,0xbf97bf0b,0x3f49bfa7,
0x3f0b3f80,0xbfa73f80,0xbfa73f80,0xbf0bbf80,0xbf0b3fb5,0xbfa70000,0xbfa70000,0x3f0bbfb5,0xbfa73f80,0xbf0bbf80,0xbf0bbf80,0x3fa7bf80,0xbfa70000,0x3f0bbfb5,0x3f0bbfb5,0x3fa70000,
0x3e8d3f80,0xbfb23f80,0xbfb23f80,0xbe8dbf80,0xbf973fa7,0xbf49bf0b,0xbf49bf0b,0x3f97bfa7,0xbf970000,0x3f49bfb5,0x3f49bfb5,0x3f970000,0x3e8dbfa7,0x3fb2bf0b,0x3fb2bf0b,0xbe8d3fa7,
0x3f80,0xbfb53f80,0xbfb53f80,0xbf80,0xbfb53f80,0xbf80,0xbf80,0x3fb5bf80,0xbf80,0x3fb5bf80,0x3fb5bf80,0x3f80,0x3fb5bf80,0x3f80,0x3f80,0xbfb53f80,
0xbe8d3f80,0xbfb23f80,0xbfb23f80,0x3e8dbf80,0xbf973f0b,0x3f49bfa7,0x3f49bfa7,0x3f97bf0b,0x3f97bfb5,0x3f490000,0x3f490000,0xbf973fb5,0x3e8d3f0b,0xbfb23fa7,0xbfb23fa7,0xbe8dbf0b,
0xbf0b3f80,0xbfa73f80,0xbfa73f80,0x3f0bbf80,0xbf0b0000,0x3fa7bfb5,0x3fa7bfb5,0x3f0b0000,0x3fa7bf80,0xbf0b3f80,0xbf0b3f80,0xbfa73f80,0xbfa73fb5,0xbf0b0000,0xbf0b0000,0x3fa7bfb5,
0xbf493f80,0xbf973f80,0xbf973f80,0x3f49bf80,0x3e8dbf0b,0x3fb2bfa7,0x3fb2bfa7,0xbe8d3f0b,0x3e8d0000,0xbfb23fb5,0xbfb23fb5,0xbe8d0000,0xbf493f0b,0x3f97bfa7,0x3f97bfa7,0x3f49bf0b,
0xbf803f80,0xbf803f80,0xbf803f80,0x3f80bf80,0x3f80bf80,0x3f80bf80,0x3f80bf80,0xbf803f80,0xbf803f80,0xbf803f80,0xbf803f80,0x3f80bf80,0x3f80bf80,0x3f80bf80,0x3f80bf80,0xbf803f80,
0xbf973f80,0xbf493f80,0xbf493f80,0x3f97bf80,0x3fb2bfa7,0x3e8dbf0b,0x3e8dbf0b,0xbfb23fa7,0xbfb23fb5,0x3e8d0000,0x3e8d0000,0x3fb2bfb5,0x3f97bfa7,0xbf493f0b,0xbf493f0b,0xbf973fa7,
0xbfa73f80,0xbf0b3f80,0xbf0b3f80,0x3fa7bf80,0x3fa7bfb5,0xbf0b0000,0xbf0b0000,0xbfa73fb5,0xbf0b3f80,0x3fa7bf80,0x3fa7bf80,0x3f0bbf80,0xbf0b0000,0xbfa73fb5,0xbfa73fb5,0x3f0b0000,
0xbfb23f80,0xbe8d3f80,0xbe8d3f80,0x3fb2bf80,0x3f49bfa7,0xbf973f0b,0xbf973f0b,0xbf493fa7,0x3f490000,0x3f97bfb5,0x3f97bfb5,0xbf490000,0xbfb23fa7,0x3e8d3f0b,0x3e8d3f0b,0x3fb2bfa7,
0xbfb53f80,0x3f80,0x3f80,0x3fb5bf80,0xbf80,0xbfb53f80,0xbfb53f80,0x3f80,0x3fb5bf80,0xbf80,0xbf80,0xbfb53f80,0x3f80,0x3fb5bf80,0x3fb5bf80,0xbf80,
0xbfb23f80,0x3e8d3f80,0x3e8d3f80,0x3fb2bf80,0xbf49bf0b,0xbf973fa7,0xbf973fa7,0x3f493f0b,0x3f49bfb5,0xbf970000,0xbf970000,0xbf493fb5,0x3fb2bf0b,0x3e8dbfa7,0x3e8dbfa7,0xbfb23f0b,
0xbfa73f80,0x3f0b3f80,0x3f0b3f80,0x3fa7bf80,0xbfa70000,0xbf0b3fb5,0xbf0b3fb5,0x3fa70000,0xbf0bbf80,0xbfa73f80,0xbfa73f80,0x3f0b3f80,0x3f0bbfb5,0xbfa70000,0xbfa70000,0xbf0b3fb5,
0xbf973f80,0x3f493f80,0x3f493f80,0x3f97bf80,0xbfb23f0b,0x3e8d3fa7,0x3e8d3fa7,0x3fb2bf0b,0xbfb20000,0xbe8d3fb5,0xbe8d3fb5,0x3fb20000,0xbf97bf0b,0xbf493fa7,0xbf493fa7,0x3f973f0b,
0x3f803f80,0xbf803f80,0x3f80bf80,0x3f803f80,0x3f803f80,0xbf803f80,0x3f80bf80,0x3f803f80,0x3f803f80,0xbf803f80,0x3f80bf80,0x3f803f80,0x3f803f80,0xbf803f80,0x3f80bf80,0x3f803f80,
0x3f49bf80,0x3f973f80,0xbf97bf80,0x3f49bf80,0x3e8dbfa7,0x3fb23f0b,0xbfb2bf0b,0x3e8dbfa7,0xbe8dbfb5,0x3fb20000,0xbfb20000,0xbe8dbfb5,0xbf49bfa7,0x3f97bf0b,0xbf973f0b,0xbf49bfa7,
0xbfa7bf80,0x3f0bbf80,0xbf0b3f80,0xbfa7bf80,0xbfa70000,0xbf0bbfb5,0x3f0b3fb5,0xbfa70000,0xbf0b3f80,0xbfa7bf80,0x3fa73f80,0xbf0b3f80,0x3f0b3fb5,0xbfa70000,0x3fa70000,0x3f0b3fb5,
0xbe8d3f80,0xbfb2bf80,0x3fb23f80,0xbe8d3f80,0x3f973fa7,0xbf493f0b,0x3f49bf0b,0x3f973fa7,0x3f970000,0x3f493fb5,0xbf49bfb5,0x3f970000,0xbe8dbfa7,0x3fb23f0b,0xbfb2bf0b,0xbe8dbfa7,
0x3fb53f80,0x3f80,0xbf80,0x3fb53f80,0xbf80,0x3fb53f80,0xbfb5bf80,0xbf80,0xbfb5bf80,0xbf80,0x3f80,0xbfb5bf80,0x3f80,0xbfb5bf80,0x3fb53f80,0x3f80,
0xbe8dbf80,0x3fb23f80,0xbfb2bf80,0xbe8dbf80,0xbf97bf0b,0xbf49bfa7,0x3f493fa7,0xbf97bf0b,0x3f973fb5,0xbf490000,0x3f490000,0x3f973fb5,0x3e8dbf0b,0x3fb23fa7,0xbfb2bfa7,0x3e8dbf0b,
0xbfa7bf80,0xbf0bbf80,0x3f0b3f80,0xbfa7bf80,0x3fa73fb5,0xbf0b0000,0x3f0b0000,0x3fa73fb5,0xbf0bbf80,0x3fa73f80,0xbfa7bf80,0xbf0bbf80,0xbf0b0000,0xbfa7bfb5,0x3fa73fb5,0xbf0b0000,
0x3f493f80,0xbf97bf80,0x3f973f80,0x3f493f80,0xbe8dbf0b,0x3fb23fa7,0xbfb2bfa7,0xbe8dbf0b,0xbe8d0000,0xbfb2bfb5,0x3fb23fb5,0xbe8d0000,0x3f493f0b,0x3f973fa7,0xbf97bfa7,0x3f493f0b,
0x3f803f80,0x3f803f80,0xbf80bf80,0x3f803f80,0xbf80bf80,0xbf80bf80,0x3f803f80,0xbf80bf80,0x3f803f80,0x3f803f80,0xbf80bf80,0x3f803f80,0xbf80bf80,0xbf80bf80,0x3f803f80,0xbf80bf80,
0xbf97bf80,0x3f493f80,0xbf49bf80,0xbf97bf80,0x3fb23fa7,0xbe8dbf0b,0x3e8d3f0b,0x3fb23fa7,0xbfb2bfb5,0xbe8d0000,0x3e8d0000,0xbfb2bfb5,0x3f973fa7,0x3f493f0b,0xbf49bf0b,0x3f973fa7,
0xbf0bbf80,0xbfa7bf80,0x3fa73f80,0xbf0bbf80,0xbf0b0000,0x3fa73fb5,0xbfa7bfb5,0xbf0b0000,0x3fa73f80,0xbf0bbf80,0x3f0b3f80,0x3fa73f80,0xbfa7bfb5,0xbf0b0000,0x3f0b0000,0xbfa7bfb5,
0x3fb23f80,0xbe8dbf80,0x3e8d3f80,0x3fb23f80,0xbf49bfa7,0xbf97bf0b,0x3f973f0b,0xbf49bfa7,0xbf490000,0x3f973fb5,0xbf97bfb5,0xbf490000,0x3fb23fa7,0x3e8dbf0b,0xbe8d3f0b,0x3fb23fa7,
0x3f80,0x3fb53f80,0xbfb5bf80,0x3f80,0x3fb53f80,0xbf80,0x3f80,0x3fb53f80,0xbf80,0xbfb5bf80,0x3fb53f80,0xbf80,0xbfb5bf80,0x3f80,0xbf80,0xbfb5bf80,
0xbfb2bf80,0xbe8d3f80,0x3e8dbf80,0xbfb2bf80,0xbf493f0b,0x3f973fa7,0xbf97bfa7,0xbf493f0b,0x3f493fb5,0x3f970000,0xbf970000,0x3f493fb5,0x3fb23f0b,0xbe8dbfa7,0x3e8d3fa7,0x3fb23f0b,
0x3f0bbf80,0xbfa7bf80,0x3fa73f80,0x3f0bbf80,0xbf0bbfb5,0xbfa70000,0x3fa70000,0xbf0bbfb5,0xbfa7bf80,0xbf0b3f80,0x3f0bbf80,0xbfa7bf80,0xbfa70000,0x3f0b3fb5,0xbf0bbfb5,0xbfa70000,
0x3f973f80,0x3f49bf80,0xbf493f80,0x3f973f80,0x3fb23f0b,0x3e8dbfa7,0xbe8d3fa7,0x3fb23f0b,0x3fb20000,0xbe8dbfb5,0x3e8d3fb5,0x3fb20000,0x3f97bf0b,0xbf49bfa7,0x3f493fa7,0x3f97bf0b,
0x3f803f80,0xbf803f80,0xbf803f80,0xbf80bf80,0x3f803f80,0xbf803f80,0xbf803f80,0xbf80bf80,0x3f803f80,0xbf803f80,0xbf803f80,0xbf80bf80,0x3f803f80,0xbf803f80,0xbf803f80,0xbf80bf80,
0xbf973f80,0xbf49bf80,0xbf49bf80,0x3f97bf80,0xbfb23f0b,0xbe8dbfa7,0xbe8dbfa7,0x3fb2bf0b,0xbfb20000,0x3e8dbfb5,0x3e8dbfb5,0x3fb20000,0xbf97bf0b,0x3f49bfa7,0x3f49bfa7,0x3f973f0b,
0xbf0bbf80,0x3fa7bf80,0x3fa7bf80,0x3f0b3f80,0x3f0bbfb5,0x3fa70000,0x3fa70000,0xbf0b3fb5,0x3fa7bf80,0x3f0b3f80,0x3f0b3f80,0xbfa73f80,0x3fa70000,0xbf0b3fb5,0xbf0b3fb5,0xbfa70000,
0x3fb2bf80,0x3e8d3f80,0x3e8d3f80,0xbfb23f80,0x3f493f0b,0xbf973fa7,0xbf973fa7,0xbf49bf0b,0xbf493fb5,0xbf970000,0xbf970000,0x3f49bfb5,0xbfb23f0b,0x3e8dbfa7,0x3e8dbfa7,0x3fb2bf0b,
0x3f80,0xbfb53f80,0xbfb53f80,0xbf80,0xbfb53f80,0xbf80,0xbf80,0x3fb5bf80,0xbf80,0x3fb5bf80,0x3fb5bf80,0x3f80,0x3fb5bf80,0x3f80,0x3f80,0xbfb53f80,
0xbfb23f80,0x3e8dbf80,0x3e8dbf80,0x3fb2bf80,0x3f49bfa7,0x3f97bf0b,0x3f97bf0b,0xbf493fa7,0x3f490000,0xbf973fb5,0xbf973fb5,0xbf490000,0xbfb23fa7,0xbe8dbf0b,0xbe8dbf0b,0x3fb2bfa7,
0x3f0bbf80,0x3fa7bf80,0x3fa7bf80,0xbf0b3f80,0x3f0b0000,0xbfa73fb5,0xbfa73fb5,0xbf0b0000,0xbfa73f80,0x3f0bbf80,0x3f0bbf80,0x3fa7bf80,0x3fa7bfb5,0x3f0b0000,0x3f0b0000,0xbfa73fb5,
0x3f97bf80,0xbf493f80,0xbf493f80,0xbf973f80,0xbfb23fa7,0x3e8dbf0b,0x3e8dbf0b,0x3fb2bfa7,0x3fb2bfb5,0x3e8d0000,0x3e8d0000,0xbfb23fb5,0xbf973fa7,0xbf493f0b,0xbf493f0b,0x3f97bfa7,
0xbf803f80,0xbf803f80,0xbf803f80,0x3f80bf80,0x3f80bf80,0x3f80bf80,0x3f80bf80,0xbf803f80,0xbf803f80,0xbf803f80,0xbf803f80,0x3f80bf80,0x3f80bf80,0x3f80bf80,0x3f80bf80,0xbf803f80,
0xbf493f80,0x3f97bf80,0x3f97bf80,0x3f49bf80,0x3e8dbf0b,0xbfb23fa7,0xbfb23fa7,0xbe8d3f0b,0x3e8d0000,0x3fb2bfb5,0x3fb2bfb5,0xbe8d0000,0xbf493f0b,0xbf973fa7,0xbf973fa7,0x3f49bf0b,
0x3fa7bf80,0x3f0bbf80,0x3f0bbf80,0xbfa73f80,0xbfa73fb5,0x3f0b0000,0x3f0b0000,0x3fa7bfb5,0x3f0bbf80,0xbfa73f80,0xbfa73f80,0xbf0b3f80,0x3f0b0000,0x3fa7bfb5,0x3fa7bfb5,0xbf0b0000,
0x3e8dbf80,0xbfb23f80,0xbfb23f80,0xbe8d3f80,0x3f97bf0b,0x3f49bfa7,0x3f49bfa7,0xbf973f0b,0xbf973fb5,0x3f490000,0x3f490000,0x3f97bfb5,0xbe8dbf0b,0xbfb23fa7,0xbfb23fa7,0x3e8d3f0b,
0xbfb53f80,0x3f80,0x3f80,0x3fb5bf80,0xbf80,0xbfb53f80,0xbfb53f80,0x3f80,0x3fb5bf80,0xbf80,0xbf80,0xbfb53f80,0x3f80,0x3fb5bf80,0x3fb5bf80,0xbf80,
0x3e8d3f80,0x3fb2bf80,0x3fb2bf80,0xbe8dbf80,0xbf973fa7,0x3f493f0b,0x3f493f0b,0x3f97bfa7,0xbf970000,0xbf493fb5,0xbf493fb5,0x3f970000,0x3e8dbfa7,0xbfb23f0b,0xbfb23f0b,0xbe8d3fa7,
0x3fa7bf80,0xbf0bbf80,0xbf0bbf80,0xbfa73f80,0x3fa70000,0x3f0bbfb5,0x3f0bbfb5,0xbfa70000,0x3f0b3f80,0x3fa7bf80,0x3fa7bf80,0xbf0bbf80,0xbf0b3fb5,0x3fa70000,0x3fa70000,0x3f0bbfb5,
0xbf49bf80,0xbf973f80,0xbf973f80,0x3f493f80,0xbe8dbfa7,0xbfb23f0b,0xbfb23f0b,0x3e8d3fa7,0x3e8dbfb5,0xbfb20000,0xbfb20000,0xbe8d3fb5,0x3f49bfa7,0xbf97bf0b,0xbf97bf0b,0xbf493fa7,
0x3f803f80,0xbf803f80,0x3f80bf80,0x3f803f80,0x3f803f80,0xbf803f80,0x3f80bf80,0x3f803f80,0x3f803f80,0xbf803f80,0x3f80bf80,0x3f803f80,0x3f803f80,0xbf803f80,0x3f80bf80,0x3f803f80,
0xbf97bf80,0x3f49bf80,0xbf493f80,0xbf97bf80,0xbfb2bf0b,0x3e8dbfa7,0xbe8d3fa7,0xbfb2bf0b,0xbfb20000,0xbe8dbfb5,0x3e8d3fb5,0xbfb20000,0xbf973f0b,0xbf49bfa7,0x3f493fa7,0xbf973f0b,
0x3fa73f80,0xbf0b3f80,0x3f0bbf80,0x3fa73f80,0x3fa70000,0x3f0b3fb5,0xbf0bbfb5,0x3fa70000,0x3f0bbf80,0x3fa73f80,0xbfa7bf80,0x3f0bbf80,0xbf0bbfb5,0x3fa70000,0xbfa70000,0xbf0bbfb5,
0xbfb2bf80,0x3e8dbf80,0xbe8d3f80,0xbfb2bf80,0xbf493f0b,0xbf97bfa7,0x3f973fa7,0xbf493f0b,0x3f493fb5,0xbf970000,0x3f970000,0x3f493fb5,0x3fb23f0b,0x3e8d3fa7,0xbe8dbfa7,0x3fb23f0b,
0x3fb53f80,0x3f80,0xbf80,0x3fb53f80,0xbf80,0x3fb53f80,0xbfb5bf80,0xbf80,0xbfb5bf80,0xbf80,0x3f80,0xbfb5bf80,0x3f80,0xbfb5bf80,0x3fb53f80,0x3f80,
0xbfb2bf80,0xbe8dbf80,0x3e8d3f80,0xbfb2bf80,0x3f493fa7,0xbf97bf0b,0x3f973f0b,0x3f493fa7,0x3f490000,0x3f973fb5,0xbf97bfb5,0x3f490000,0xbfb2bfa7,0x3e8dbf0b,0xbe8d3f0b,0xbfb2bfa7,
0x3fa73f80,0x3f0b3f80,0xbf0bbf80,0x3fa73f80,0xbfa7bfb5,0x3f0b0000,0xbf0b0000,0xbfa7bfb5,0x3f0b3f80,0xbfa7bf80,0x3fa73f80,0x3f0b3f80,0x3f0b0000,0x3fa73fb5,0xbfa7bfb5,0x3f0b0000,
0xbf97bf80,0xbf49bf80,0x3f493f80,0xbf97bf80,0x3fb23fa7,0x3e8d3f0b,0xbe8dbf0b,0x3fb23fa7,0xbfb2bfb5,0x3e8d0000,0xbe8d0000,0xbfb2bfb5,0x3f973fa7,0xbf49bf0b,0x3f493f0b,0x3f973fa7,
0x3f803f80,0x3f803f80,0xbf80bf80,0x3f803f80,0xbf80bf80,0xbf80bf80,0x3f803f80,0xbf80bf80,0x3f803f80,0x3f803f80,0xbf80bf80,0x3f803f80,0xbf80bf80,0xbf80bf80,0x3f803f80,0xbf80bf80,
0xbf49bf80,0xbf97bf80,0x3f973f80,0xbf49bf80,0x3e8d3f0b,0x3fb23fa7,0xbfb2bfa7,0x3e8d3f0b,0x3e8d0000,0xbfb2bfb5,0x3fb23fb5,0x3e8d0000,0xbf49bf0b,0x3f973fa7,0xbf97bfa7,0xbf49bf0b,
0x3f0b3f80,0x3fa73f80,0xbfa7bf80,0x3f0b3f80,0x3f0b0000,0xbfa7bfb5,0x3fa73fb5,0x3f0b0000,0xbfa7bf80,0x3f0b3f80,0xbf0bbf80,0xbfa7bf80,0x3fa73fb5,0x3f0b0000,0xbf0b0000,0x3fa73fb5,
0xbe8dbf80,0xbfb2bf80,0x3fb23f80,0xbe8dbf80,0xbf97bf0b,0x3f493fa7,0xbf49bfa7,0xbf97bf0b,0x3f973fb5,0x3f490000,0xbf490000,0x3f973fb5,0x3e8dbf0b,0xbfb2bfa7,0x3fb23fa7,0x3e8dbf0b,
0x3f80,0x3fb53f80,0xbfb5bf80,0x3f80,0x3fb53f80,0xbf80,0x3f80,0x3fb53f80,0xbf80,0xbfb5bf80,0x3fb53f80,0xbf80,0xbfb5bf80,0x3f80,0xbf80,0xbfb5bf80,
0x3e8dbf80,0xbfb2bf80,0x3fb23f80,0x3e8dbf80,0xbf97bfa7,0xbf493f0b,0x3f49bf0b,0xbf97bfa7,0xbf970000,0x3f493fb5,0xbf49bfb5,0xbf970000,0x3e8d3fa7,0x3fb23f0b,0xbfb2bf0b,0x3e8d3fa7,
0xbf0b3f80,0x3fa73f80,0xbfa7bf80,0xbf0b3f80,0x3f0b3fb5,0x3fa70000,0xbfa70000,0x3f0b3fb5,0x3fa73f80,0x3f0bbf80,0xbf0b3f80,0x3fa73f80,0x3fa70000,0xbf0bbfb5,0x3f0b3fb5,0x3fa70000,
0x3f49bf80,0xbf97bf80,0x3f973f80,0x3f49bf80,0x3e8dbfa7,0xbfb2bf0b,0x3fb23f0b,0x3e8dbfa7,0xbe8dbfb5,0xbfb20000,0x3fb20000,0xbe8dbfb5,0xbf49bfa7,0xbf973f0b,0x3f97bf0b,0xbf49bfa7,
0x3f803f80,0xbf803f80,0xbf803f80,0xbf80bf80,0x3f803f80,0xbf803f80,0xbf803f80,0xbf80bf80,0x3f803f80,0xbf803f80,0xbf803f80,0xbf80bf80,0x3f803f80,0xbf803f80,0xbf803f80,0xbf80bf80,
0xbf49bf80,0x3f97bf80,0x3f97bf80,0x3f493f80,0xbe8dbfa7,0x3fb2bf0b,0x3fb2bf0b,0x3e8d3fa7,0x3e8dbfb5,0x3fb20000,0x3fb20000,0xbe8d3fb5,0x3f49bfa7,0x3f973f0b,0x3f973f0b,0xbf493fa7,
0x3f0b3f80,0xbfa73f80,0xbfa73f80,0xbf0bbf80,0xbf0b3fb5,0xbfa70000,0xbfa70000,0x3f0bbfb5,0xbfa73f80,0xbf0bbf80,0xbf0bbf80,0x3fa7bf80,0xbfa70000,0x3f0bbfb5,0x3f0bbfb5,0x3fa70000,
0xbe8dbf80,0x3fb2bf80,0x3fb2bf80,0x3e8d3f80,0x3f97bfa7,0x3f493f0b,0x3f493f0b,0xbf973fa7,0x3f970000,0xbf493fb5,0xbf493fb5,0xbf970000,0xbe8d3fa7,0xbfb23f0b,0xbfb23f0b,0x3e8dbfa7,
0x3f80,0xbfb53f80,0xbfb53f80,0xbf80,0xbfb53f80,0xbf80,0xbf80,0x3fb5bf80,0xbf80,0x3fb5bf80,0x3fb5bf80,0x3f80,0x3fb5bf80,0x3f80,0x3f80,0xbfb53f80,
0x3e8dbf80,0x3fb2bf80,0x3fb2bf80,0xbe8d3f80,0x3f97bf0b,0xbf493fa7,0xbf493fa7,0xbf973f0b,0xbf973fb5,0xbf490000,0xbf490000,0x3f97bfb5,0xbe8dbf0b,0x3fb2bfa7,0x3fb2bfa7,0x3e8d3f0b,
0xbf0b3f80,0xbfa73f80,0xbfa73f80,0x3f0bbf80,0xbf0b0000,0x3fa7bfb5,0x3fa7bfb5,0x3f0b0000,0x3fa7bf80,0xbf0b3f80,0xbf0b3f80,0xbfa73f80,0xbfa73fb5,0xbf0b0000,0xbf0b0000,0x3fa7bfb5,
0x3f49bf80,0x3f97bf80,0x3f97bf80,0xbf493f80,0xbe8d3f0b,0xbfb23fa7,0xbfb23fa7,0x3e8dbf0b,0xbe8d0000,0x3fb2bfb5,0x3fb2bfb5,0x3e8d0000,0x3f49bf0b,0xbf973fa7,0xbf973fa7,0xbf493f0b,
0xbf803f80,0xbf803f80,0xbf803f80,0x3f80bf80,0x3f80bf80,0x3f80bf80,0x3f80bf80,0xbf803f80,0xbf803f80,0xbf803f80,0xbf803f80,0x3f80bf80,0x3f80bf80,0x3f80bf80,0x3f80bf80,0xbf803f80,
0x3f97bf80,0x3f49bf80,0x3f49bf80,0xbf973f80,0xbfb23fa7,0xbe8d3f0b,0xbe8d3f0b,0x3fb2bfa7,0x3fb2bfb5,0xbe8d0000,0xbe8d0000,0xbfb23fb5,0xbf973fa7,0x3f49bf0b,0x3f49bf0b,0x3f97bfa7,
0xbfa73f80,0xbf0b3f80,0xbf0b3f80,0x3fa7bf80,0x3fa7bfb5,0xbf0b0000,0xbf0b0000,0xbfa73fb5,0xbf0b3f80,0x3fa7bf80,0x3fa7bf80,0x3f0bbf80,0xbf0b0000,0xbfa73fb5,0xbfa73fb5,0x3f0b0000,
0x3fb2bf80,0x3e8dbf80,0x3e8dbf80,0xbfb23f80,0xbf493fa7,0x3f97bf0b,0x3f97bf0b,0x3f49bfa7,0xbf490000,0xbf973fb5,0xbf973fb5,0x3f490000,0x3fb2bfa7,0xbe8dbf0b,0xbe8dbf0b,0xbfb23fa7,
0xbfb53f80,0x3f80,0x3f80,0x3fb5bf80,0xbf80,0xbfb53f80,0xbfb53f80,0x3f80,0x3fb5bf80,0xbf80,0xbf80,0xbfb53f80,0x3f80,0x3fb5bf80,0x3fb5bf80,0xbf80,
0x3fb2bf80,0xbe8dbf80,0xbe8dbf80,0xbfb23f80,0x3f493f0b,0x3f97bfa7,0x3f97bfa7,0xbf49bf0b,0xbf493fb5,0x3f970000,0x3f970000,0x3f49bfb5,0xbfb23f0b,0xbe8d3fa7,0xbe8d3fa7,0x3fb2bf0b,
0xbfa73f80,0x3f0b3f80,0x3f0b3f80,0x3fa7bf80,0xbfa70000,0xbf0b3fb5,0xbf0b3fb5,0x3fa70000,0xbf0bbf80,0xbfa73f80,0xbfa73f80,0x3f0b3f80,0x3f0bbfb5,0xbfa70000,0xbfa70000,0xbf0b3fb5,
0x3f97bf80,0xbf49bf80,0xbf49bf80,0xbf973f80,0x3fb2bf0b,0xbe8dbfa7,0xbe8dbfa7,0xbfb23f0b,0x3fb20000,0x3e8dbfb5,0x3e8dbfb5,0xbfb20000,0x3f973f0b,0x3f49bfa7,0x3f49bfa7,0xbf97bf0b,
0x3f803f80,0xbf803f80,0x3f80bf80,0x3f803f80,0x3f803f80,0xbf803f80,0x3f80bf80,0x3f803f80,0x3f803f80,0xbf803f80,0x3f80bf80,0x3f803f80,0x3f803f80,0xbf803f80,0x3f80bf80,0x3f803f80,
0xbf493f80,0xbf97bf80,0x3f973f80,0xbf493f80,0xbe8d3fa7,0xbfb2bf0b,0x3fb23f0b,0xbe8d3fa7,0x3e8d3fb5,0xbfb20000,0x3fb20000,0x3e8d3fb5,0x3f493fa7,0xbf973f0b,0x3f97bf0b,0x3f493fa7,
0xbfa7bf80,0x3f0bbf80,0xbf0b3f80,0xbfa7bf80,0xbfa70000,0xbf0bbfb5,0x3f0b3fb5,0xbfa70000,0xbf0b3f80,0xbfa7bf80,0x3fa73f80,0xbf0b3f80,0x3f0b3fb5,0xbfa70000,0x3fa70000,0x3f0b3fb5,
0x3e8dbf80,0x3fb23f80,0xbfb2bf80,0x3e8dbf80,0xbf97bfa7,0x3f49bf0b,0xbf493f0b,0xbf97bfa7,0xbf970000,0xbf49bfb5,0x3f493fb5,0xbf970000,0x3e8d3fa7,0xbfb2bf0b,0x3fb23f0b,0x3e8d3fa7,
0x3fb53f80,0x3f80,0xbf80,0x3fb53f80,0xbf80,0x3fb53f80,0xbfb5bf80,0xbf80,0xbfb5bf80,0xbf80,0x3f80,0xbfb5bf80,0x3f80,0xbfb5bf80,0x3fb53f80,0x3f80,
0x3e8d3f80,0xbfb2bf80,0x3fb23f80,0x3e8d3f80,0x3f973f0b,0x3f493fa7,0xbf49bfa7,0x3f973f0b,0xbf97bfb5,0x3f490000,0xbf490000,0xbf97bfb5,0xbe8d3f0b,0xbfb2bfa7,0x3fb23fa7,0xbe8d3f0b,
0xbfa7bf80,0xbf0bbf80,0x3f0b3f80,0xbfa7bf80,0x3fa73fb5,0xbf0b0000,0x3f0b0000,0x3fa73fb5,0xbf0bbf80,0x3fa73f80,0xbfa7bf80,0xbf0bbf80,0xbf0b0000,0xbfa7bfb5,0x3fa73fb5,0xbf0b0000,
0xbf49bf80,0x3f973f80,0xbf97bf80,0xbf49bf80,0x3e8d3f0b,0xbfb2bfa7,0x3fb23fa7,0x3e8d3f0b,0x3e8d0000,0x3fb23fb5,0xbfb2bfb5,0x3e8d0000,0xbf49bf0b,0xbf97bfa7,0x3f973fa7,0xbf49bf0b,
0x3f803f80,0x3f803f80,0xbf80bf80,0x3f803f80,0xbf80bf80,0xbf80bf80,0x3f803f80,0xbf80bf80,0x3f803f80,0x3f803f80,0xbf80bf80,0x3f803f80,0xbf80bf80,0xbf80bf80,0x3f803f80,0xbf80bf80,
0x3f973f80,0xbf49bf80,0x3f493f80,0x3f973f80,0xbfb2bfa7,0x3e8d3f0b,0xbe8dbf0b,0xbfb2bfa7,0x3fb23fb5,0x3e8d0000,0xbe8d0000,0x3fb23fb5,0xbf97bfa7,0xbf49bf0b,0x3f493f0b,0xbf97bfa7,
0xbf0bbf80,0xbfa7bf80,0x3fa73f80,0xbf0bbf80,0xbf0b0000,0x3fa73fb5,0xbfa7bfb5,0xbf0b0000,0x3fa73f80,0xbf0bbf80,0x3f0b3f80,0x3fa73f80,0xbfa7bfb5,0xbf0b0000,0x3f0b0000,0xbfa7bfb5,
0xbfb2bf80,0x3e8d3f80,0xbe8dbf80,0xbfb2bf80,0x3f493fa7,0x3f973f0b,0xbf97bf0b,0x3f493fa7,0x3f490000,0xbf97bfb5,0x3f973fb5,0x3f490000,0xbfb2bfa7,0xbe8d3f0b,0x3e8dbf0b,0xbfb2bfa7,
0x3f80,0x3fb53f80,0xbfb5bf80,0x3f80,0x3fb53f80,0xbf80,0x3f80,0x3fb53f80,0xbf80,0xbfb5bf80,0x3fb53f80,0xbf80,0xbfb5bf80,0x3f80,0xbf80,0xbfb5bf80,
0x3fb23f80,0x3e8dbf80,0xbe8d3f80,0x3fb23f80,0x3f49bf0b,0xbf97bfa7,0x3f973fa7,0x3f49bf0b,0xbf49bfb5,0xbf970000,0x3f970000,0xbf49bfb5,0xbfb2bf0b,0x3e8d3fa7,0xbe8dbfa7,0xbfb2bf0b,
0x3f0bbf80,0xbfa7bf80,0x3fa73f80,0x3f0bbf80,0xbf0bbfb5,0xbfa70000,0x3fa70000,0xbf0bbfb5,0xbfa7bf80,0xbf0b3f80,0x3f0bbf80,0xbfa7bf80,0xbfa70000,0x3f0b3fb5,0xbf0bbfb5,0xbfa70000,
0xbf97bf80,0xbf493f80,0x3f49bf80,0xbf97bf80,0xbfb2bf0b,0xbe8d3fa7,0x3e8dbfa7,0xbfb2bf0b,0xbfb20000,0x3e8d3fb5,0xbe8dbfb5,0xbfb20000,0xbf973f0b,0x3f493fa7,0xbf49bfa7,0xbf973f0b,
0x3f803f80,0xbf803f80,0xbf803f80,0xbf80bf80,0x3f803f80,0xbf803f80,0xbf803f80,0xbf80bf80,0x3f803f80,0xbf803f80,0xbf803f80,0xbf80bf80,0x3f803f80,0xbf803f80,0xbf803f80,0xbf80bf80,
0x3f97bf80,0x3f493f80,0x3f493f80,0xbf973f80,0x3fb2bf0b,0x3e8d3fa7,0x3e8d3fa7,0xbfb23f0b,0x3fb20000,0xbe8d3fb5,0xbe8d3fb5,0xbfb20000,0x3f973f0b,0xbf493fa7,0xbf493fa7,0xbf97bf0b,
0xbf0bbf80,0x3fa7bf80,0x3fa7bf80,0x3f0b3f80,0x3f0bbfb5,0x3fa70000,0x3fa70000,0xbf0b3fb5,0x3fa7bf80,0x3f0b3f80,0x3f0b3f80,0xbfa73f80,0x3fa70000,0xbf0b3fb5,0xbf0b3fb5,0xbfa70000,
0xbfb23f80,0xbe8dbf80,0xbe8dbf80,0x3fb2bf80,0xbf49bf0b,0x3f97bfa7,0x3f97bfa7,0x3f493f0b,0x3f49bfb5,0x3f970000,0x3f970000,0xbf493fb5,0x3fb2bf0b,0xbe8d3fa7,0xbe8d3fa7,0xbfb23f0b,
0x3f80,0xbfb53f80,0xbfb53f80,0xbf80,0xbfb53f80,0xbf80,0xbf80,0x3fb5bf80,0xbf80,0x3fb5bf80,0x3fb5bf80,0x3f80,0x3fb5bf80,0x3f80,0x3f80,0xbfb53f80,
0x3fb2bf80,0xbe8d3f80,0xbe8d3f80,0xbfb23f80,0xbf493fa7,0xbf973f0b,0xbf973f0b,0x3f49bfa7,0xbf490000,0x3f97bfb5,0x3f97bfb5,0x3f490000,0x3fb2bfa7,0x3e8d3f0b,0x3e8d3f0b,0xbfb23fa7,
0x3f0bbf80,0x3fa7bf80,0x3fa7bf80,0xbf0b3f80,0x3f0b0000,0xbfa73fb5,0xbfa73fb5,0xbf0b0000,0xbfa73f80,0x3f0bbf80,0x3f0bbf80,0x3fa7bf80,0x3fa7bfb5,0x3f0b0000,0x3f0b0000,0xbfa73fb5,
0xbf973f80,0x3f49bf80,0x3f49bf80,0x3f97bf80,0x3fb2bfa7,0xbe8d3f0b,0xbe8d3f0b,0xbfb23fa7,0xbfb23fb5,0xbe8d0000,0xbe8d0000,0x3fb2bfb5,0x3f97bfa7,0x3f49bf0b,0x3f49bf0b,0xbf973fa7,
0xbf803f80,0xbf803f80,0xbf803f80,0x3f80bf80,0x3f80bf80,0x3f80bf80,0x3f80bf80,0xbf803f80,0xbf803f80,0xbf803f80,0xbf803f80,0x3f80bf80,0x3f80bf80,0x3f80bf80,0x3f80bf80,0xbf803f80,
0x3f49bf80,0xbf973f80,0xbf973f80,0xbf493f80,0xbe8d3f0b,0x3fb2bfa7,0x3fb2bfa7,0x3e8dbf0b,0xbe8d0000,0xbfb23fb5,0xbfb23fb5,0x3e8d0000,0x3f49bf0b,0x3f97bfa7,0x3f97bfa7,0xbf493f0b,
0x3fa7bf80,0x3f0bbf80,0x3f0bbf80,0xbfa73f80,0xbfa73fb5,0x3f0b0000,0x3f0b0000,0x3fa7bfb5,0x3f0bbf80,0xbfa73f80,0xbfa73f80,0xbf0b3f80,0x3f0b0000,0x3fa7bfb5,0x3fa7bfb5,0xbf0b0000,
0xbe8d3f80,0x3fb2bf80,0x3fb2bf80,0x3e8dbf80,0xbf973f0b,0xbf493fa7,0xbf493fa7,0x3f97bf0b,0x3f97bfb5,0xbf490000,0xbf490000,0xbf973fb5,0x3e8d3f0b,0x3fb2bfa7,0x3fb2bfa7,0xbe8dbf0b,
0xbfb53f80,0x3f80,0x3f80,0x3fb5bf80,0xbf80,0xbfb53f80,0xbfb53f80,0x3f80,0x3fb5bf80,0xbf80,0xbf80,0xbfb53f80,0x3f80,0x3fb5bf80,0x3fb5bf80,0xbf80,
0xbe8dbf80,0xbfb23f80,0xbfb23f80,0x3e8d3f80,0x3f97bfa7,0xbf49bf0b,0xbf49bf0b,0xbf973fa7,0x3f970000,0x3f49bfb5,0x3f49bfb5,0xbf970000,0xbe8d3fa7,0x3fb2bf0b,0x3fb2bf0b,0x3e8dbfa7,
0x3fa7bf80,0xbf0bbf80,0xbf0bbf80,0xbfa73f80,0x3fa70000,0x3f0bbfb5,0x3f0bbfb5,0xbfa70000,0x3f0b3f80,0x3fa7bf80,0x3fa7bf80,0xbf0bbf80,0xbf0b3fb5,0x3fa70000,0x3fa70000,0x3f0bbfb5,
0x3f493f80,0x3f97bf80,0x3f97bf80,0xbf49bf80,0x3e8d3fa7,0x3fb2bf0b,0x3fb2bf0b,0xbe8dbfa7,0xbe8d3fb5,0x3fb20000,0x3fb20000,0x3e8dbfb5,0xbf493fa7,0x3f973f0b,0x3f973f0b,0x3f49bfa7,
0x3f803f80,0xbf803f80,0,0,0x3f803f80,0xbf803f80,0,0,0x3f803f80,0xbf803f80,0,0,0x3f803f80,0xbf803f80,0,0,
0x3f7b3f80,0xbf7b3f80,0xbe480000,0x3e480000,0x3f553f6d,0xbf553f6d,0xbf0ebec4,0x3f0ebec4,0x3f0e3f35,0xbf0e3f35,0xbf55bf35,0x3f55bf35,0x3e483ec4,0xbe483ec4,0xbf7bbf6d,0x3f7bbf6d,
0x3f6d3f80,0xbf6d3f80,0xbec40000,0x3ec40000,0x3ec43f35,0xbec43f35,0xbf6dbf35,0x3f6dbf35,0xbec40000,0x3ec40000,0xbf6dbf80,0x3f6dbf80,0xbf6dbf35,0x3f6dbf35,0xbec4bf35,0x3ec4bf35,
0x3f553f80,0xbf553f80,0xbf0e0000,0x3f0e0000,0xbe483ec4,0x3e483ec4,0xbf7bbf6d,0x3f7bbf6d,0xbf7bbf35,0x3f7bbf35,0xbe48bf35,0x3e48bf35,0xbf0ebf6d,0x3f0ebf6d,0x3f553ec4,0xbf553ec4,
0x3f353f80,0xbf353f80,0xbf350000,0x3f350000,0xbf350000,0x3f350000,0xbf35bf80,0x3f35bf80,0xbf35bf80,0x3f35bf80,0x3f350000,0xbf350000,0x3f350000,0xbf350000,0x3f353f80,0xbf353f80,
0x3f0e3f80,0xbf0e3f80,0xbf550000,0x3f550000,0xbf7bbec4,0x3f7bbec4,0xbe48bf6d,0x3e48bf6d,0x3e48bf35,0xbe48bf35,0x3f7b3f35,0xbf7b3f35,0x3f553f6d,0xbf553f6d,0xbf0e3ec4,0x3f0e3ec4,
0x3ec43f80,0xbec43f80,0xbf6d0000,0x3f6d0000,0xbf6dbf35,0x3f6dbf35,0x3ec4bf35,0xbec4bf35,0x3f6d0000,0xbf6d0000,0x3ec43f80,0xbec43f80,0xbec43f35,0x3ec43f35,0xbf6dbf35,0x3f6dbf35,
0x3e483f80,0xbe483f80,0xbf7b0000,0x3f7b0000,0xbf0ebf6d,0x3f0ebf6d,0x3f55bec4,0xbf55bec4,0x3f553f35,0xbf553f35,0xbf0e3f35,0x3f0e3f35,0xbf7bbec4,0x3f7bbec4,0x3e48bf6d,0xbe48bf6d,
0x3f80,0x3f80,0xbf800000,0x3f800000,0xbf80,0xbf80,0x3f800000,0xbf800000,0x3f80,0x3f80,0xbf800000,0x3f800000,0xbf80,0xbf80,0x3f800000,0xbf800000,
0xbe483f80,0x3e483f80,0xbf7b0000,0x3f7b0000,0x3f0ebf6d,0xbf0ebf6d,0x3f553ec4,0xbf553ec4,0xbf553f35,0x3f553f35,0xbf0ebf35,0x3f0ebf35,0x3f7bbec4,0xbf7bbec4,0x3e483f6d,0xbe483f6d,
0xbec43f80,0x3ec43f80,0xbf6d0000,0x3f6d0000,0x3f6dbf35,0xbf6dbf35,0x3ec43f35,0xbec43f35,0xbf6d0000,0x3f6d0000,0x3ec4bf80,0xbec4bf80,0x3ec43f35,0xbec43f35,0xbf6d3f35,0x3f6d3f35,
0xbf0e3f80,0x3f0e3f80,0xbf550000,0x3f550000,0x3f7bbec4,0xbf7bbec4,0xbe483f6d,0x3e483f6d,0xbe48bf35,0x3e48bf35,0x3f7bbf35,0xbf7bbf35,0xbf553f6d,0x3f553f6d,0xbf0ebec4,0x3f0ebec4,
0xbf353f80,0x3f353f80,0xbf350000,0x3f350000,0x3f350000,0xbf350000,0xbf353f80,0x3f353f80,0x3f35bf80,0xbf35bf80,0x3f350000,0xbf350000,0xbf350000,0x3f350000,0x3f35bf80,0xbf35bf80,
0xbf553f80,0x3f553f80,0xbf0e0000,0x3f0e0000,0x3e483ec4,0xbe483ec4,0xbf7b3f6d,0x3f7b3f6d,0x3f7bbf35,0xbf7bbf35,0xbe483f35,0x3e483f35,0x3f0ebf6d,0xbf0ebf6d,0x3f55bec4,0xbf55bec4,
0xbf6d3f80,0x3f6d3f80,0xbec40000,0x3ec40000,0xbec43f35,0x3ec43f35,0xbf6d3f35,0x3f6d3f35,0x3ec40000,0xbec40000,0xbf6d3f80,0x3f6d3f80,0x3f6dbf35,0xbf6dbf35,0xbec43f35,0x3ec43f35,
0xbf7b3f80,0x3f7b3f80,0xbe480000,0x3e480000,0xbf553f6d,0x3f553f6d,0xbf0e3ec4,0x3f0e3ec4,0xbf0e3f35,0x3f0e3f35,0xbf553f35,0x3f553f35,0xbe483ec4,0x3e483ec4,0xbf7b3f6d,0x3f7b3f6d,
0x3f803f80,0xbf803f80,0,0,0x3f803f80,0xbf803f80,0,0,0x3f803f80,0xbf803f80,0,0,0x3f803f80,0xbf803f80,0,0,
0x3f7b3f80,0xbf7b3f80,0xbe480000,0x3e480000,0x3f553f6d,0xbf553f6d,0xbf0ebec4,0x3f0ebec4,0x3f0e3f35,0xbf0e3f35,0xbf55bf35,0x3f55bf35,0x3e483ec4,0xbe483ec4,0xbf7bbf6d,0x3f7bbf6d,
0x3f6d3f80,0xbf6d3f80,0xbec40000,0x3ec40000,0x3ec43f35,0xbec43f35,0xbf6dbf35,0x3f6dbf35,0xbec40000,0x3ec40000,0xbf6dbf80,0x3f6dbf80,0xbf6dbf35,0x3f6dbf35,0xbec4bf35,0x3ec4bf35,
0x3f553f80,0xbf553f80,0xbf0e0000,0x3f0e0000,0xbe483ec4,0x3e483ec4,0xbf7bbf6d,0x3f7bbf6d,0xbf7bbf35,0x3f7bbf35,0xbe48bf35,0x3e48bf35,0xbf0ebf6d,0x3f0ebf6d,0x3f553ec4,0xbf553ec4,
0x3f353f80,0xbf353f80,0xbf350000,0x3f350000,0xbf350000,0x3f350000,0xbf35bf80,0x3f35bf80,0xbf35bf80,0x3f35bf80,0x3f350000,0xbf350000,0x3f350000,0xbf350000,0x3f353f80,0xbf353f80,
0x3f0e3f80,0xbf0e3f80,0xbf550000,0x3f550000,0xbf7bbec4,0x3f7bbec4,0xbe48bf6d,0x3e48bf6d,0x3e48bf35,0xbe48bf35,0x3f7b3f35,0xbf7b3f35,0x3f553f6d,0xbf553f6d,0xbf0e3ec4,0x3f0e3ec4,
0x3ec43f80,0xbec43f80,0xbf6d0000,0x3f6d0000,0xbf6dbf35,0x3f6dbf35,0x3ec4bf35,0xbec4bf35,0x3f6d0000,0xbf6d0000,0x3ec43f80,0xbec43f80,0xbec43f35,0x3ec43f35,0xbf6dbf35,0x3f6dbf35,
0x3e483f80,0xbe483f80,0xbf7b0000,0x3f7b0000,0xbf0ebf6d,0x3f0ebf6d,0x3f55bec4,0xbf55bec4,0x3f553f35,0xbf553f35,0xbf0e3f35,0x3f0e3f35,0xbf7bbec4,0x3f7bbec4,0x3e48bf6d,0xbe48bf6d,
0x3f80,0x3f80,0xbf800000,0x3f800000,0xbf80,0xbf80,0x3f800000,0xbf800000,0x3f80,0x3f80,0xbf800000,0x3f800000,0xbf80,0xbf80,0x3f800000,0xbf800000,
0xbe483f80,0x3e483f80,0xbf7b0000,0x3f7b0000,0x3f0ebf6d,0xbf0ebf6d,0x3f553ec4,0xbf553ec4,0xbf553f35,0x3f553f35,0xbf0ebf35,0x3f0ebf35,0x3f7bbec4,0xbf7bbec4,0x3e483f6d,0xbe483f6d,
0xbec43f80,0x3ec43f80,0xbf6d0000,0x3f6d0000,0x3f6dbf35,0xbf6dbf35,0x3ec43f35,0xbec43f35,0xbf6d0000,0x3f6d0000,0x3ec4bf80,0xbec4bf80,0x3ec43f35,0xbec43f35,0xbf6d3f35,0x3f6d3f35,
0xbf0e3f80,0x3f0e3f80,0xbf550000,0x3f550000,0x3f7bbec4,0xbf7bbec4,0xbe483f6d,0x3e483f6d,0xbe48bf35,0x3e48bf35,0x3f7bbf35,0xbf7bbf35,0xbf553f6d,0x3f553f6d,0xbf0ebec4,0x3f0ebec4,
0xbf353f80,0x3f353f80,0xbf350000,0x3f350000,0x3f350000,0xbf350000,0xbf353f80,0x3f353f80,0x3f35bf80,0xbf35bf80,0x3f350000,0xbf350000,0xbf350000,0x3f350000,0x3f35bf80,0xbf35bf80,
0xbf553f80,0x3f553f80,0xbf0e0000,0x3f0e0000,0x3e483ec4,0xbe483ec4,0xbf7b3f6d,0x3f7b3f6d,0x3f7bbf35,0xbf7bbf35,0xbe483f35,0x3e483f35,0x3f0ebf6d,0xbf0ebf6d,0x3f55bec4,0xbf55bec4,
0xbf6d3f80,0x3f6d3f80,0xbec40000,0x3ec40000,0xbec43f35,0x3ec43f35,0xbf6d3f35,0x3f6d3f35,0x3ec40000,0xbec40000,0xbf6d3f80,0x3f6d3f80,0x3f6dbf35,0xbf6dbf35,0xbec43f35,0x3ec43f35,
0xbf7b3f80,0x3f7b3f80,0xbe480000,0x3e480000,0xbf553f6d,0x3f553f6d,0xbf0e3ec4,0x3f0e3ec4,0xbf0e3f35,0x3f0e3f35,0xbf553f35,0x3f553f35,0xbe483ec4,0x3e483ec4,0xbf7b3f6d,0x3f7b3f6d,
0x3f803f80,0xbf803f80,0,0,0x3f803f80,0xbf803f80,0,0,0x3f803f80,0xbf803f80,0,0,0x3f803f80,0xbf803f80,0,0,
0xbe480000,0x3e480000,0xbf7bbf80,0x3f7bbf80,0xbf0ebec4,0x3f0ebec4,0xbf55bf6d,0x3f55bf6d,0xbf55bf35,0x3f55bf35,0xbf0ebf35,0x3f0ebf35,0xbf7bbf6d,0x3f7bbf6d,0xbe48bec4,0x3e48bec4,
0xbf6dbf80,0x3f6dbf80,0x3ec40000,0xbec40000,0xbec4bf35,0x3ec4bf35,0x3f6d3f35,0xbf6d3f35,0x3ec40000,0xbec40000,0x3f6d3f80,0xbf6d3f80,0x3f6d3f35,0xbf6d3f35,0x3ec43f35,0xbec43f35,
0x3f0e0000,0xbf0e0000,0x3f553f80,0xbf553f80,0x3f7b3f6d,0xbf7b3f6d,0xbe483ec4,0x3e483ec4,0x3e483f35,0xbe483f35,0xbf7bbf35,0x3f7bbf35,0xbf55bec4,0x3f55bec4,0xbf0ebf6d,0x3f0ebf6d,
0x3f353f80,0xbf353f80,0xbf350000,0x3f350000,0xbf350000,0x3f350000,0xbf35bf80,0x3f35bf80,0xbf35bf80,0x3f35bf80,0x3f350000,0xbf350000,0x3f350000,0xbf350000,0x3f353f80,0xbf353f80,
0xbf550000,0x3f550000,0xbf0ebf80,0x3f0ebf80,0xbe48bf6d,0x3e48bf6d,0x3f7b3ec4,0xbf7b3ec4,0x3f7b3f35,0xbf7b3f35,0xbe483f35,0x3e483f35,0xbf0e3ec4,0x3f0e3ec4,0xbf55bf6d,0x3f55bf6d,
0xbec4bf80,0x3ec4bf80,0x3f6d0000,0xbf6d0000,0x3f6d3f35,0xbf6d3f35,0xbec43f35,0x3ec43f35,0xbf6d0000,0x3f6d0000,0xbec4bf80,0x3ec4bf80,0x3ec4bf35,0xbec4bf35,0x3f6d3f35,0xbf6d3f35,
0x3f7b0000,0xbf7b0000,0x3e483f80,0xbe483f80,0xbf553ec4,0x3f553ec4,0xbf0ebf6d,0x3f0ebf6d,0x3f0ebf35,0xbf0ebf35,0x3f553f35,0xbf553f35,0xbe483f6d,0x3e483f6d,0xbf7bbec4,0x3f7bbec4,
0x3f80,0x3f80,0xbf800000,0x3f800000,0xbf80,0xbf80,0x3f800000,0xbf800000,0x3f80,0x3f80,0xbf800000,0x3f800000,0xbf80,0xbf80,0x3f800000,0xbf800000,
0xbf7b0000,0x3f7b0000,0x3e48bf80,0xbe48bf80,0x3f553ec4,0xbf553ec4,0xbf0e3f6d,0x3f0e3f6d,0xbf0ebf35,0x3f0ebf35,0x3f55bf35,0xbf55bf35,0x3e483f6d,0xbe483f6d,0xbf7b3ec4,0x3f7b3ec4,
0x3ec4bf80,0xbec4bf80,0x3f6d0000,0xbf6d0000,0xbf6d3f35,0x3f6d3f35,0xbec4bf35,0x3ec4bf35,0x3f6d0000,0xbf6d0000,0xbec43f80,0x3ec43f80,0xbec4bf35,0x3ec4bf35,0x3f6dbf35,0xbf6dbf35,
0x3f550000,0xbf550000,0xbf0e3f80,0x3f0e3f80,0x3e48bf6d,0xbe48bf6d,0x3f7bbec4,0xbf7bbec4,0xbf7b3f35,0x3f7b3f35,0xbe48bf35,0x3e48bf35,0x3f0e3ec4,0xbf0e3ec4,0xbf553f6d,0x3f553f6d,
0xbf353f80,0x3f353f80,0xbf350000,0x3f350000,0x3f350000,0xbf350000,0xbf353f80,0x3f353f80,0x3f35bf80,0xbf35bf80,0x3f350000,0xbf350000,0xbf350000,0x3f350000,0x3f35bf80,0xbf35bf80,
0xbf0e0000,0x3f0e0000,0x3f55bf80,0xbf55bf80,0xbf7b3f6d,0x3f7b3f6d,0xbe48bec4,0x3e48bec4,0xbe483f35,0x3e483f35,0xbf7b3f35,0x3f7b3f35,0x3f55bec4,0xbf55bec4,0xbf0e3f6d,0x3f0e3f6d,
0x3f6dbf80,0xbf6dbf80,0x3ec40000,0xbec40000,0x3ec4bf35,0xbec4bf35,0x3f6dbf35,0xbf6dbf35,0xbec40000,0x3ec40000,0x3f6dbf80,0xbf6dbf80,0xbf6d3f35,0x3f6d3f35,0x3ec4bf35,0xbec4bf35,
0x3e480000,0xbe480000,0xbf7b3f80,0x3f7b3f80,0x3f0ebec4,0xbf0ebec4,0xbf553f6d,0x3f553f6d,0x3f55bf35,0xbf55bf35,0xbf0e3f35,0x3f0e3f35,0x3f7bbf6d,0xbf7bbf6d,0xbe483ec4,0x3e483ec4,
0x3f803f80,0xbf803f80,0,0,0x3f803f80,0xbf803f80,0,0,0x3f803f80,0xbf803f80,0,0,0x3f803f80,0xbf803f80,0,0,
0xbe480000,0x3e480000,0xbf7bbf80,0x3f7bbf80,0xbf0ebec4,0x3f0ebec4,0xbf55bf6d,0x3f55bf6d,0xbf55bf35,0x3f55bf35,0xbf0ebf35,0x3f0ebf35,0xbf7bbf6d,0x3f7bbf6d,0xbe48bec4,0x3e48bec4,
0xbf6dbf80,0x3f6dbf80,0x3ec40000,0xbec40000,0xbec4bf35,0x3ec4bf35,0x3f6d3f35,0xbf6d3f35,0x3ec40000,0xbec40000,0x3f6d3f80,0xbf6d3f80,0x3f6d3f35,0xbf6d3f35,0x3ec43f35,0xbec43f35,
0x3f0e0000,0xbf0e0000,0x3f553f80,0xbf553f80,0x3f7b3f6d,0xbf7b3f6d,0xbe483ec4,0x3e483ec4,0x3e483f35,0xbe483f35,0xbf7bbf35,0x3f7bbf35,0xbf55bec4,0x3f55bec4,0xbf0ebf6d,0x3f0ebf6d,
0x3f353f80,0xbf353f80,0xbf350000,0x3f350000,0xbf350000,0x3f350000,0xbf35bf80,0x3f35bf80,0xbf35bf80,0x3f35bf80,0x3f350000,0xbf350000,0x3f350000,0xbf350000,0x3f353f80,0xbf353f80,
0xbf550000,0x3f550000,0xbf0ebf80,0x3f0ebf80,0xbe48bf6d,0x3e48bf6d,0x3f7b3ec4,0xbf7b3ec4,0x3f7b3f35,0xbf7b3f35,0xbe483f35,0x3e483f35,0xbf0e3ec4,0x3f0e3ec4,0xbf55bf6d,0x3f55bf6d,
0xbec4bf80,0x3ec4bf80,0x3f6d0000,0xbf6d0000,0x3f6d3f35,0xbf6d3f35,0xbec43f35,0x3ec43f35,0xbf6d0000,0x3f6d0000,0xbec4bf80,0x3ec4bf80,0x3ec4bf35,0xbec4bf35,0x3f6d3f35,0xbf6d3f35,
0x3f7b0000,0xbf7b0000,0x3e483f80,0xbe483f80,0xbf553ec4,0x3f553ec4,0xbf0ebf6d,0x3f0ebf6d,0x3f0ebf35,0xbf0ebf35,0x3f553f35,0xbf553f35,0xbe483f6d,0x3e483f6d,0xbf7bbec4,0x3f7bbec4,
0x3f80,0x3f80,0xbf800000,0x3f800000,0xbf80,0xbf80,0x3f800000,0xbf800000,0x3f80,0x3f80,0xbf800000,0x3f800000,0xbf80,0xbf80,0x3f800000,0xbf800000,
0xbf7b0000,0x3f7b0000,0x3e48bf80,0xbe48bf80,0x3f553ec4,0xbf553ec4,0xbf0e3f6d,0x3f0e3f6d,0xbf0ebf35,0x3f0ebf35,0x3f55bf35,0xbf55bf35,0x3e483f6d,0xbe483f6d,0xbf7b3ec4,0x3f7b3ec4,
0x3ec4bf80,0xbec4bf80,0x3f6d0000,0xbf6d0000,0xbf6d3f35,0x3f6d3f35,0xbec4bf35,0x3ec4bf35,0x3f6d0000,0xbf6d0000,0xbec43f80,0x3ec43f80,0xbec4bf35,0x3ec4bf35,0x3f6dbf35,0xbf6dbf35,
0x3f550000,0xbf550000,0xbf0e3f80,0x3f0e3f80,0x3e48bf6d,0xbe48bf6d,0x3f7bbec4,0xbf7bbec4,0xbf7b3f35,0x3f7b3f35,0xbe48bf35,0x3e48bf35,0x3f0e3ec4,0xbf0e3ec4,0xbf553f6d,0x3f553f6d,
0xbf353f80,0x3f353f80,0xbf350000,0x3f350000,0x3f350000,0xbf350000,0xbf353f80,0x3f353f80,0x3f35bf80,0xbf35bf80,0x3f350000,0xbf350000,0xbf350000,0x3f350000,0x3f35bf80,0xbf35bf80,
0xbf0e0000,0x3f0e0000,0x3f55bf80,0xbf55bf80,0xbf7b3f6d,0x3f7b3f6d,0xbe48bec4,0x3e48bec4,0xbe483f35,0x3e483f35,0xbf7b3f35,0x3f7b3f35,0x3f55bec4,0xbf55bec4,0xbf0e3f6d,0x3f0e3f6d,
0x3f6dbf80,0xbf6dbf80,0x3ec40000,0xbec40000,0x3ec4bf35,0xbec4bf35,0x3f6dbf35,0xbf6dbf35,0xbec40000,0x3ec40000,0x3f6dbf80,0xbf6dbf80,0xbf6d3f35,0x3f6d3f35,0x3ec4bf35,0xbec4bf35,
0x3e480000,0xbe480000,0xbf7b3f80,0x3f7b3f80,0x3f0ebec4,0xbf0ebec4,0xbf553f6d,0x3f553f6d,0x3f55bf35,0xbf55bf35,0xbf0e3f35,0x3f0e3f35,0x3f7bbf6d,0xbf7bbf6d,0xbe483ec4,0x3e483ec4,
0x3f803f80,0xbf803f80,0,0,0x3f803f80,0xbf803f80,0,0,0x3f803f80,0xbf803f80,0,0,0x3f803f80,0xbf803f80,0,0,
0xbf7bbf80,0x3f7bbf80,0x3e480000,0xbe480000,0xbf55bf6d,0x3f55bf6d,0x3f0e3ec4,0xbf0e3ec4,0xbf0ebf35,0x3f0ebf35,0x3f553f35,0xbf553f35,0xbe48bec4,0x3e48bec4,0x3f7b3f6d,0xbf7b3f6d,
0x3f6d3f80,0xbf6d3f80,0xbec40000,0x3ec40000,0x3ec43f35,0xbec43f35,0xbf6dbf35,0x3f6dbf35,0xbec40000,0x3ec40000,0xbf6dbf80,0x3f6dbf80,0xbf6dbf35,0x3f6dbf35,0xbec4bf35,0x3ec4bf35,
0xbf55bf80,0x3f55bf80,0x3f0e0000,0xbf0e0000,0x3e48bec4,0xbe48bec4,0x3f7b3f6d,0xbf7b3f6d,0x3f7b3f35,0xbf7b3f35,0x3e483f35,0xbe483f35,0x3f0e3f6d,0xbf0e3f6d,0xbf55bec4,0x3f55bec4,
0x3f353f80,0xbf353f80,0xbf350000,0x3f350000,0xbf350000,0x3f350000,0xbf35bf80,0x3f35bf80,0xbf35bf80,0x3f35bf80,0x3f350000,0xbf350000,0x3f350000,0xbf350000,0x3f353f80,0xbf353f80,
0xbf0ebf80,0x3f0ebf80,0x3f550000,0xbf550000,0x3f7b3ec4,0xbf7b3ec4,0x3e483f6d,0xbe483f6d,0xbe483f35,0x3e483f35,0xbf7bbf35,0x3f7bbf35,0xbf55bf6d,0x3f55bf6d,0x3f0ebec4,0xbf0ebec4,
0x3ec43f80,0xbec43f80,0xbf6d0000,0x3f6d0000,0xbf6dbf35,0x3f6dbf35,0x3ec4bf35,0xbec4bf35,0x3f6d0000,0xbf6d0000,0x3ec43f80,0xbec43f80,0xbec43f35,0x3ec43f35,0xbf6dbf35,0x3f6dbf35,
0xbe48bf80,0x3e48bf80,0x3f7b0000,0xbf7b0000,0x3f0e3f6d,0xbf0e3f6d,0xbf553ec4,0x3f553ec4,0xbf55bf35,0x3f55bf35,0x3f0ebf35,0xbf0ebf35,0x3f7b3ec4,0xbf7b3ec4,0xbe483f6d,0x3e483f6d,
0x3f80,0x3f80,0xbf800000,0x3f800000,0xbf80,0xbf80,0x3f800000,0xbf800000,0x3f80,0x3f80,0xbf800000,0x3f800000,0xbf80,0xbf80,0x3f800000,0xbf800000,
0x3e48bf80,0xbe48bf80,0x3f7b0000,0xbf7b0000,0xbf0e3f6d,0x3f0e3f6d,0xbf55bec4,0x3f55bec4,0x3f55bf35,0xbf55bf35,0x3f0e3f35,0xbf0e3f35,0xbf7b3ec4,0x3f7b3ec4,0xbe48bf6d,0x3e48bf6d,
0xbec43f80,0x3ec43f80,0xbf6d0000,0x3f6d0000,0x3f6dbf35,0xbf6dbf35,0x3ec43f35,0xbec43f35,0xbf6d0000,0x3f6d0000,0x3ec4bf80,0xbec4bf80,0x3ec43f35,0xbec43f35,0xbf6d3f35,0x3f6d3f35,
0x3f0ebf80,0xbf0ebf80,0x3f550000,0xbf550000,0xbf7b3ec4,0x3f7b3ec4,0x3e48bf6d,0xbe48bf6d,0x3e483f35,0xbe483f35,0xbf7b3f35,0x3f7b3f35,0x3f55bf6d,0xbf55bf6d,0x3f0e3ec4,0xbf0e3ec4,
0xbf353f80,0x3f353f80,0xbf350000,0x3f350000,0x3f350000,0xbf350000,0xbf353f80,0x3f353f80,0x3f35bf80,0xbf35bf80,0x3f350000,0xbf350000,0xbf350000,0x3f350000,0x3f35bf80,0xbf35bf80,
0x3f55bf80,0xbf55bf80,0x3f0e0000,0xbf0e0000,0xbe48bec4,0x3e48bec4,0x3f7bbf6d,0xbf7bbf6d,0xbf7b3f35,0x3f7b3f35,0x3e48bf35,0xbe48bf35,0xbf0e3f6d,0x3f0e3f6d,0xbf553ec4,0x3f553ec4,
0xbf6d3f80,0x3f6d3f80,0xbec40000,0x3ec40000,0xbec43f35,0x3ec43f35,0xbf6d3f35,0x3f6d3f35,0x3ec40000,0xbec40000,0xbf6d3f80,0x3f6d3f80,0x3f6dbf35,0xbf6dbf35,0xbec43f35,0x3ec43f35,
0x3f7bbf80,0xbf7bbf80,0x3e480000,0xbe480000,0x3f55bf6d,0xbf55bf6d,0x3f0ebec4,0xbf0ebec4,0x3f0ebf35,0xbf0ebf35,0x3f55bf35,0xbf55bf35,0x3e48bec4,0xbe48bec4,0x3f7bbf6d,0xbf7bbf6d,
0x3f803f80,0xbf803f80,0,0,0x3f803f80,0xbf803f80,0,0,0x3f803f80,0xbf803f80,0,0,0x3f803f80,0xbf803f80,0,0,
0xbf7bbf80,0x3f7bbf80,0x3e480000,0xbe480000,0xbf55bf6d,0x3f55bf6d,0x3f0e3ec4,0xbf0e3ec4,0xbf0ebf35,0x3f0ebf35,0x3f553f35,0xbf553f35,0xbe48bec4,0x3e48bec4,0x3f7b3f6d,0xbf7b3f6d,
0x3f6d3f80,0xbf6d3f80,0xbec40000,0x3ec40000,0x3ec43f35,0xbec43f35,0xbf6dbf35,0x3f6dbf35,0xbec40000,0x3ec40000,0xbf6dbf80,0x3f6dbf80,0xbf6dbf35,0x3f6dbf35,0xbec4bf35,0x3ec4bf35,
0xbf55bf80,0x3f55bf80,0x3f0e0000,0xbf0e0000,0x3e48bec4,0xbe48bec4,0x3f7b3f6d,0xbf7b3f6d,0x3f7b3f35,0xbf7b3f35,0x3e483f35,0xbe483f35,0x3f0e3f6d,0xbf0e3f6d,0xbf55bec4,0x3f55bec4,
0x3f353f80,0xbf353f80,0xbf350000,0x3f350000,0xbf350000,0x3f350000,0xbf35bf80,0x3f35bf80,0xbf35bf80,0x3f35bf80,0x3f350000,0xbf350000,0x3f350000,0xbf350000,0x3f353f80,0xbf353f80,
0xbf0ebf80,0x3f0ebf80,0x3f550000,0xbf550000,0x3f7b3ec4,0xbf7b3ec4,0x3e483f6d,0xbe483f6d,0xbe483f35,0x3e483f35,0xbf7bbf35,0x3f7bbf35,0xbf55bf6d,0x3f55bf6d,0x3f0ebec4,0xbf0ebec4,
0x3ec43f80,0xbec43f80,0xbf6d0000,0x3f6d0000,0xbf6dbf35,0x3f6dbf35,0x3ec4bf35,0xbec4bf35,0x3f6d0000,0xbf6d0000,0x3ec43f80,0xbec43f80,0xbec43f35,0x3ec43f35,0xbf6dbf35,0x3f6dbf35,
0xbe48bf80,0x3e48bf80,0x3f7b0000,0xbf7b0000,0x3f0e3f6d,0xbf0e3f6d,0xbf553ec4,0x3f553ec4,0xbf55bf35,0x3f55bf35,0x3f0ebf35,0xbf0ebf35,0x3f7b3ec4,0xbf7b3ec4,0xbe483f6d,0x3e483f6d,
0x3f80,0x3f80,0xbf800000,0x3f800000,0xbf80,0xbf80,0x3f800000,0xbf800000,0x3f80,0x3f80,0xbf800000,0x3f800000,0xbf80,0xbf80,0x3f800000,0xbf800000,
0x3e48bf80,0xbe48bf80,0x3f7b0000,0xbf7b0000,0xbf0e3f6d,0x3f0e3f6d,0xbf55bec4,0x3f55bec4,0x3f55bf35,0xbf55bf35,0x3f0e3f35,0xbf0e3f35,0xbf7b3ec4,0x3f7b3ec4,0xbe48bf6d,0x3e48bf6d,
0xbec43f80,0x3ec43f80,0xbf6d0000,0x3f6d0000,0x3f6dbf35,0xbf6dbf35,0x3ec43f35,0xbec43f35,0xbf6d0000,0x3f6d0000,0x3ec4bf80,0xbec4bf80,0x3ec43f35,0xbec43f35,0xbf6d3f35,0x3f6d3f35,
0x3f0ebf80,0xbf0ebf80,0x3f550000,0xbf550000,0xbf7b3ec4,0x3f7b3ec4,0x3e48bf6d,0xbe48bf6d,0x3e483f35,0xbe483f35,0xbf7b3f35,0x3f7b3f35,0x3f55bf6d,0xbf55bf6d,0x3f0e3ec4,0xbf0e3ec4,
0xbf353f80,0x3f353f80,0xbf350000,0x3f350000,0x3f350000,0xbf350000,0xbf353f80,0x3f353f80,0x3f35bf80,0xbf35bf80,0x3f350000,0xbf350000,0xbf350000,0x3f350000,0x3f35bf80,0xbf35bf80,
0x3f55bf80,0xbf55bf80,0x3f0e0000,0xbf0e0000,0xbe48bec4,0x3e48bec4,0x3f7bbf6d,0xbf7bbf6d,0xbf7b3f35,0x3f7b3f35,0x3e48bf35,0xbe48bf35,0xbf0e3f6d,0x3f0e3f6d,0xbf553ec4,0x3f553ec4,
0xbf6d3f80,0x3f6d3f80,0xbec40000,0x3ec40000,0xbec43f35,0x3ec43f35,0xbf6d3f35,0x3f6d3f35,0x3ec40000,0xbec40000,0xbf6d3f80,0x3f6d3f80,0x3f6dbf35,0xbf6dbf35,0xbec43f35,0x3ec43f35,
0x3f7bbf80,0xbf7bbf80,0x3e480000,0xbe480000,0x3f55bf6d,0xbf55bf6d,0x3f0ebec4,0xbf0ebec4,0x3f0ebf35,0xbf0ebf35,0x3f55bf35,0xbf55bf35,0x3e48bec4,0xbe48bec4,0x3f7bbf6d,0xbf7bbf6d,
0x3f803f80,0xbf803f80,0,0,0x3f803f80,0xbf803f80,0,0,0x3f803f80,0xbf803f80,0,0,0x3f803f80,0xbf803f80,0,0,
0x3e480000,0xbe480000,0x3f7b3f80,0xbf7b3f80,0x3f0e3ec4,0xbf0e3ec4,0x3f553f6d,0xbf553f6d,0x3f553f35,0xbf553f35,0x3f0e3f35,0xbf0e3f35,0x3f7b3f6d,0xbf7b3f6d,0x3e483ec4,0xbe483ec4,
0xbf6dbf80,0x3f6dbf80,0x3ec40000,0xbec40000,0xbec4bf35,0x3ec4bf35,0x3f6d3f35,0xbf6d3f35,0x3ec40000,0xbec40000,0x3f6d3f80,0xbf6d3f80,0x3f6d3f35,0xbf6d3f35,0x3ec43f35,0xbec43f35,
0xbf0e0000,0x3f0e0000,0xbf55bf80,0x3f55bf80,0xbf7bbf6d,0x3f7bbf6d,0x3e48bec4,0xbe48bec4,0xbe48bf35,0x3e48bf35,0x3f7b3f35,0xbf7b3f35,0x3f553ec4,0xbf553ec4,0x3f0e3f6d,0xbf0e3f6d,
0x3f353f80,0xbf353f80,0xbf350000,0x3f350000,0xbf350000,0x3f350000,0xbf35bf80,0x3f35bf80,0xbf35bf80,0x3f35bf80,0x3f350000,0xbf350000,0x3f350000,0xbf350000,0x3f353f80,0xbf353f80,
0x3f550000,0xbf550000,0x3f0e3f80,0xbf0e3f80,0x3e483f6d,0xbe483f6d,0xbf7bbec4,0x3f7bbec4,0xbf7bbf35,0x3f7bbf35,0x3e48bf35,0xbe48bf35,0x3f0ebec4,0xbf0ebec4,0x3f553f6d,0xbf553f6d,
0xbec4bf80,0x3ec4bf80,0x3f6d0000,0xbf6d0000,0x3f6d3f35,0xbf6d3f35,0xbec43f35,0x3ec43f35,0xbf6d0000,0x3f6d0000,0xbec4bf80,0x3ec4bf80,0x3ec4bf35,0xbec4bf35,0x3f6d3f35,0xbf6d3f35,
0xbf7b0000,0x3f7b0000,0xbe48bf80,0x3e48bf80,0x3f55bec4,0xbf55bec4,0x3f0e3f6d,0xbf0e3f6d,0xbf0e3f35,0x3f0e3f35,0xbf55bf35,0x3f55bf35,0x3e48bf6d,0xbe48bf6d,0x3f7b3ec4,0xbf7b3ec4,
0x3f80,0x3f80,0xbf800000,0x3f800000,0xbf80,0xbf80,0x3f800000,0xbf800000,0x3f80,0x3f80,0xbf800000,0x3f800000,0xbf80,0xbf80,0x3f800000,0xbf800000,
0x3f7b0000,0xbf7b0000,0xbe483f80,0x3e483f80,0xbf55bec4,0x3f55bec4,0x3f0ebf6d,0xbf0ebf6d,0x3f0e3f35,0xbf0e3f35,0xbf553f35,0x3f553f35,0xbe48bf6d,0x3e48bf6d,0x3f7bbec4,0xbf7bbec4,
0x3ec4bf80,0xbec4bf80,0x3f6d0000,0xbf6d0000,0xbf6d3f35,0x3f6d3f35,0xbec4bf35,0x3ec4bf35,0x3f6d0000,0xbf6d0000,0xbec43f80,0x3ec43f80,0xbec4bf35,0x3ec4bf35,0x3f6dbf35,0xbf6dbf35,
0xbf550000,0x3f550000,0x3f0ebf80,0xbf0ebf80,0xbe483f6d,0x3e483f6d,0xbf7b3ec4,0x3f7b3ec4,0x3f7bbf35,0xbf7bbf35,0x3e483f35,0xbe483f35,0xbf0ebec4,0x3f0ebec4,0x3f55bf6d,0xbf55bf6d,
0xbf353f80,0x3f353f80,0xbf350000,0x3f350000,0x3f350000,0xbf350000,0xbf353f80,0x3f353f80,0x3f35bf80,0xbf35bf80,0x3f350000,0xbf350000,0xbf350000,0x3f350000,0x3f35bf80,0xbf35bf80,
0x3f0e0000,0xbf0e0000,0xbf553f80,0x3f553f80,0x3f7bbf6d,0xbf7bbf6d,0x3e483ec4,0xbe483ec4,0x3e48bf35,0xbe48bf35,0x3f7bbf35,0xbf7bbf35,0xbf553ec4,0x3f553ec4,0x3f0ebf6d,0xbf0ebf6d,
0x3f6dbf80,0xbf6dbf80,0x3ec40000,0xbec40000,0x3ec4bf35,0xbec4bf35,0x3f6dbf35,0xbf6dbf35,0xbec40000,0x3ec40000,0x3f6dbf80,0xbf6dbf80,0xbf6d3f35,0x3f6d3f35,0x3ec4bf35,0xbec4bf35,
0xbe480000,0x3e480000,0x3f7bbf80,0xbf7bbf80,0xbf0e3ec4,0x3f0e3ec4,0x3f55bf6d,0xbf55bf6d,0xbf553f35,0x3f553f35,0x3f0ebf35,0xbf0ebf35,0xbf7b3f6d,0x3f7b3f6d,0x3e48bec4,0xbe48bec4,
0x3f803f80,0xbf803f80,0,0,0x3f803f80,0xbf803f80,0,0,0x3f803f80,0xbf803f80,0,0,0x3f803f80,0xbf803f80,0,0,
0x3e480000,0xbe480000,0x3f7b3f80,0xbf7b3f80,0x3f0e3ec4,0xbf0e3ec4,0x3f553f6d,0xbf553f6d,0x3f553f35,0xbf553f35,0x3f0e3f35,0xbf0e3f35,0x3f7b3f6d,0xbf7b3f6d,0x3e483ec4,0xbe483ec4,
0xbf6dbf80,0x3f6dbf80,0x3ec40000,0xbec40000,0xbec4bf35,0x3ec4bf35,0x3f6d3f35,0xbf6d3f35,0x3ec40000,0xbec40000,0x3f6d3f80,0xbf6d3f80,0x3f6d3f35,0xbf6d3f35,0x3ec43f35,0xbec43f35,
0xbf0e0000,0x3f0e0000,0xbf55bf80,0x3f55bf80,0xbf7bbf6d,0x3f7bbf6d,0x3e48bec4,0xbe48bec4,0xbe48bf35,0x3e48bf35,0x3f7b3f35,0xbf7b3f35,0x3f553ec4,0xbf553ec4,0x3f0e3f6d,0xbf0e3f6d,
0x3f353f80,0xbf353f80,0xbf350000,0x3f350000,0xbf350000,0x3f350000,0xbf35bf80,0x3f35bf80,0xbf35bf80,0x3f35bf80,0x3f350000,0xbf350000,0x3f350000,0xbf350000,0x3f353f80,0xbf353f80,
0x3f550000,0xbf550000,0x3f0e3f80,0xbf0e3f80,0x3e483f6d,0xbe483f6d,0xbf7bbec4,0x3f7bbec4,0xbf7bbf35,0x3f7bbf35,0x3e48bf35,0xbe48bf35,0x3f0ebec4,0xbf0ebec4,0x3f553f6d,0xbf553f6d,
0xbec4bf80,0x3ec4bf80,0x3f6d0000,0xbf6d0000,0x3f6d3f35,0xbf6d3f35,0xbec43f35,0x3ec43f35,0xbf6d0000,0x3f6d0000,0xbec4bf80,0x3ec4bf80,0x3ec4bf35,0xbec4bf35,0x3f6d3f35,0xbf6d3f35,
0xbf7b0000,0x3f7b0000,0xbe48bf80,0x3e48bf80,0x3f55bec4,0xbf55bec4,0x3f0e3f6d,0xbf0e3f6d,0xbf0e3f35,0x3f0e3f35,0xbf55bf35,0x3f55bf35,0x3e48bf6d,0xbe48bf6d,0x3f7b3ec4,0xbf7b3ec4,
0x3f80,0x3f80,0xbf800000,0x3f800000,0xbf80,0xbf80,0x3f800000,0xbf800000,0x3f80,0x3f80,0xbf800000,0x3f800000,0xbf80,0xbf80,0x3f800000,0xbf800000,
0x3f7b0000,0xbf7b0000,0xbe483f80,0x3e483f80,0xbf55bec4,0x3f55bec4,0x3f0ebf6d,0xbf0ebf6d,0x3f0e3f35,0xbf0e3f35,0xbf553f35,0x3f553f35,0xbe48bf6d,0x3e48bf6d,0x3f7bbec4,0xbf7bbec4,
0x3ec4bf80,0xbec4bf80,0x3f6d0000,0xbf6d0000,0xbf6d3f35,0x3f6d3f35,0xbec4bf35,0x3ec4bf35,0x3f6d0000,0xbf6d0000,0xbec43f80,0x3ec43f80,0xbec4bf35,0x3ec4bf35,0x3f6dbf35,0xbf6dbf35,
0xbf550000,0x3f550000,0x3f0ebf80,0xbf0ebf80,0xbe483f6d,0x3e483f6d,0xbf7b3ec4,0x3f7b3ec4,0x3f7bbf35,0xbf7bbf35,0x3e483f35,0xbe483f35,0xbf0ebec4,0x3f0ebec4,0x3f55bf6d,0xbf55bf6d,
0xbf353f80,0x3f353f80,0xbf350000,0x3f350000,0x3f350000,0xbf350000,0xbf353f80,0x3f353f80,0x3f35bf80,0xbf35bf80,0x3f350000,0xbf350000,0xbf350000,0x3f350000,0x3f35bf80,0xbf35bf80,
0x3f0e0000,0xbf0e0000,0xbf553f80,0x3f553f80,0x3f7bbf6d,0xbf7bbf6d,0x3e483ec4,0xbe483ec4,0x3e48bf35,0xbe48bf35,0x3f7bbf35,0xbf7bbf35,0xbf553ec4,0x3f553ec4,0x3f0ebf6d,0xbf0ebf6d,
0x3f6dbf80,0xbf6dbf80,0x3ec40000,0xbec40000,0x3ec4bf35,0xbec4bf35,0x3f6dbf35,0xbf6dbf35,0xbec40000,0x3ec40000,0x3f6dbf80,0xbf6dbf80,0xbf6d3f35,0x3f6d3f35,0x3ec4bf35,0xbec4bf35,
0xbe480000,0x3e480000,0x3f7bbf80,0xbf7bbf80,0xbf0e3ec4,0x3f0e3ec4,0x3f55bf6d,0xbf55bf6d,0xbf553f35,0x3f553f35,0x3f0ebf35,0xbf0ebf35,0xbf7b3f6d,0x3f7b3f6d,0x3e48bec4,0xbe48bec4,
0x3f803f80,0,0x3f803f80,0,0x3f803f80,0,0x3f803f80,0,0x3f803f80,0,0x3f803f80,0,0x3f803f80,0,0x3f803f80,0,
0x3f7b3f80,0x3e480000,0xbe480000,0x3f7b3f80,0x3f553f6d,0x3f0e3ec4,0xbf0ebec4,0x3f553f6d,0x3f0e3f35,0x3f553f35,0xbf55bf35,0x3f0e3f35,0x3e483ec4,0x3f7b3f6d,0xbf7bbf6d,0x3e483ec4,
0x3f6d3f80,0x3ec40000,0xbf6dbf80,0xbec40000,0x3ec43f35,0x3f6d3f35,0xbec4bf35,0xbf6dbf35,0xbec40000,0x3f6d3f80,0x3ec40000,0xbf6dbf80,0xbf6dbf35,0x3ec43f35,0x3f6d3f35,0xbec4bf35,
0x3f553f80,0x3f0e0000,0x3f0e0000,0xbf55bf80,0xbe483ec4,0x3f7b3f6d,0x3f7b3f6d,0x3e48bec4,0xbf7bbf35,0x3e483f35,0x3e483f35,0x3f7b3f35,0xbf0ebf6d,0xbf55bec4,0xbf55bec4,0x3f0e3f6d,
0x3f353f80,0x3f350000,0x3f353f80,0x3f350000,0xbf350000,0x3f353f80,0xbf350000,0x3f353f80,0xbf35bf80,0xbf350000,0xbf35bf80,0xbf350000,0x3f350000,0xbf35bf80,0x3f350000,0xbf35bf80,
0x3f0e3f80,0x3f550000,0xbf550000,0x3f0e3f80,0xbf7bbec4,0x3e483f6d,0xbe48bf6d,0xbf7bbec4,0x3e48bf35,0xbf7bbf35,0x3f7b3f35,0x3e48bf35,0x3f553f6d,0x3f0ebec4,0xbf0e3ec4,0x3f553f6d,
0x3ec43f80,0x3f6d0000,0xbec4bf80,0xbf6d0000,0xbf6dbf35,0xbec43f35,0x3f6d3f35,0x3ec4bf35,0x3f6d0000,0xbec4bf80,0xbf6d0000,0x3ec43f80,0xbec43f35,0x3f6d3f35,0x3ec4bf35,0xbf6dbf35,
0x3e483f80,0x3f7b0000,0x3f7b0000,0xbe48bf80,0xbf0ebf6d,0xbf553ec4,0xbf553ec4,0x3f0e3f6d,0x3f553f35,0x3f0ebf35,0x3f0ebf35,0xbf55bf35,0xbf7bbec4,0xbe483f6d,0xbe483f6d,0x3f7b3ec4,
0x3f80,0x3f800000,0x3f80,0x3f800000,0xbf80,0xbf800000,0xbf80,0xbf800000,0x3f80,0x3f800000,0x3f80,0x3f800000,0xbf80,0xbf800000,0xbf80,0xbf800000,
0xbe483f80,0x3f7b0000,0xbf7b0000,0xbe483f80,0x3f0ebf6d,0xbf55bec4,0x3f553ec4,0x3f0ebf6d,0xbf553f35,0x3f0e3f35,0xbf0ebf35,0xbf553f35,0x3f7bbec4,0xbe48bf6d,0x3e483f6d,0x3f7bbec4,
0xbec43f80,0x3f6d0000,0x3ec4bf80,0xbf6d0000,0x3f6dbf35,0xbec4bf35,0xbf6d3f35,0x3ec43f35,0xbf6d0000,0xbec43f80,0x3f6d0000,0x3ec4bf80,0x3ec43f35,0x3f6dbf35,0xbec4bf35,0xbf6d3f35,
0xbf0e3f80,0x3f550000,0x3f550000,0x3f0ebf80,0x3f7bbec4,0x3e48bf6d,0x3e48bf6d,0xbf7b3ec4,0xbe48bf35,0xbf7b3f35,0xbf7b3f35,0x3e483f35,0xbf553f6d,0x3f0e3ec4,0x3f0e3ec4,0x3f55bf6d,
0xbf353f80,0x3f350000,0xbf353f80,0x3f350000,0x3f350000,0x3f35bf80,0x3f350000,0x3f35bf80,0x3f35bf80,0xbf350000,0x3f35bf80,0xbf350000,0xbf350000,0xbf353f80,0xbf350000,0xbf353f80,
0xbf553f80,0x3f0e0000,0xbf0e0000,0xbf553f80,0x3e483ec4,0x3f7bbf6d,0xbf7b3f6d,0x3e483ec4,0x3f7bbf35,0x3e48bf35,0xbe483f35,0x3f7bbf35,0x3f0ebf6d,0xbf553ec4,0x3f55bec4,0x3f0ebf6d,
0xbf6d3f80,0x3ec40000,0x3f6dbf80,0xbec40000,0xbec43f35,0x3f6dbf35,0x3ec4bf35,0xbf6d3f35,0x3ec40000,0x3f6dbf80,0xbec40000,0xbf6d3f80,0x3f6dbf35,0x3ec4bf35,0xbf6d3f35,0xbec43f35,
0xbf7b3f80,0x3e480000,0x3e480000,0x3f7bbf80,0xbf553f6d,0x3f0ebec4,0x3f0ebec4,0x3f55bf6d,0xbf0e3f35,0x3f55bf35,0x3f55bf35,0x3f0ebf35,0xbe483ec4,0x3f7bbf6d,0x3f7bbf6d,0x3e48bec4,
0xbf803f80,0,0xbf803f80,0,0xbf803f80,0,0xbf803f80,0,0xbf803f80,0,0xbf803f80,0,0xbf803f80,0,0xbf803f80,0,
0xbf7b3f80,0xbe480000,0x3e480000,0xbf7b3f80,0xbf553f6d,0xbf0e3ec4,0x3f0ebec4,0xbf553f6d,0xbf0e3f35,0xbf553f35,0x3f55bf35,0xbf0e3f35,0xbe483ec4,0xbf7b3f6d,0x3f7bbf6d,0xbe483ec4,
0xbf6d3f80,0xbec40000,0x3f6dbf80,0x3ec40000,0xbec43f35,0xbf6d3f35,0x3ec4bf35,0x3f6dbf35,0x3ec40000,0xbf6d3f80,0xbec40000,0x3f6dbf80,0x3f6dbf35,0xbec43f35,0xbf6d3f35,0x3ec4bf35,
0xbf553f80,0xbf0e0000,0xbf0e0000,0x3f55bf80,0x3e483ec4,0xbf7b3f6d,0xbf7b3f6d,0xbe48bec4,0x3f7bbf35,0xbe483f35,0xbe483f35,0xbf7b3f35,0x3f0ebf6d,0x3f55bec4,0x3f55bec4,0xbf0e3f6d,
0xbf353f80,0xbf350000,0xbf353f80,0xbf350000,0x3f350000,0xbf353f80,0x3f350000,0xbf353f80,0x3f35bf80,0x3f350000,0x3f35bf80,0x3f350000,0xbf350000,0x3f35bf80,0xbf350000,0x3f35bf80,
0xbf0e3f80,0xbf550000,0x3f550000,0xbf0e3f80,0x3f7bbec4,0xbe483f6d,0x3e48bf6d,0x3f7bbec4,0xbe48bf35,0x3f7bbf35,0xbf7b3f35,0xbe48bf35,0xbf553f6d,0xbf0ebec4,0x3f0e3ec4,0xbf553f6d,
0xbec43f80,0xbf6d0000,0x3ec4bf80,0x3f6d0000,0x3f6dbf35,0x3ec43f35,0xbf6d3f35,0xbec4bf35,0xbf6d0000,0x3ec4bf80,0x3f6d0000,0xbec43f80,0x3ec43f35,0xbf6d3f35,0xbec4bf35,0x3f6dbf35,
0xbe483f80,0xbf7b0000,0xbf7b0000,0x3e48bf80,0x3f0ebf6d,0x3f553ec4,0x3f553ec4,0xbf0e3f6d,0xbf553f35,0xbf0ebf35,0xbf0ebf35,0x3f55bf35,0x3f7bbec4,0x3e483f6d,0x3e483f6d,0xbf7b3ec4,
0x3f80,0xbf800000,0x3f80,0xbf800000,0xbf80,0x3f800000,0xbf80,0x3f800000,0x3f80,0xbf800000,0x3f80,0xbf800000,0xbf80,0x3f800000,0xbf80,0x3f800000,
0x3e483f80,0xbf7b0000,0x3f7b0000,0x3e483f80,0xbf0ebf6d,0x3f55bec4,0xbf553ec4,0xbf0ebf6d,0x3f553f35,0xbf0e3f35,0x3f0ebf35,0x3f553f35,0xbf7bbec4,0x3e48bf6d,0xbe483f6d,0xbf7bbec4,
0x3ec43f80,0xbf6d0000,0xbec4bf80,0x3f6d0000,0xbf6dbf35,0x3ec4bf35,0x3f6d3f35,0xbec43f35,0x3f6d0000,0x3ec43f80,0xbf6d0000,0xbec4bf80,0xbec43f35,0xbf6dbf35,0x3ec4bf35,0x3f6d3f35,
0x3f0e3f80,0xbf550000,0xbf550000,0xbf0ebf80,0xbf7bbec4,0xbe48bf6d,0xbe48bf6d,0x3f7b3ec4,0x3e48bf35,0x3f7b3f35,0x3f7b3f35,0xbe483f35,0x3f553f6d,0xbf0e3ec4,0xbf0e3ec4,0xbf55bf6d,
0x3f353f80,0xbf350000,0x3f353f80,0xbf350000,0xbf350000,0xbf35bf80,0xbf350000,0xbf35bf80,0xbf35bf80,0x3f350000,0xbf35bf80,0x3f350000,0x3f350000,0x3f353f80,0x3f350000,0x3f353f80,
0x3f553f80,0xbf0e0000,0x3f0e0000,0x3f553f80,0xbe483ec4,0xbf7bbf6d,0x3f7b3f6d,0xbe483ec4,0xbf7bbf35,0xbe48bf35,0x3e483f35,0xbf7bbf35,0xbf0ebf6d,0x3f553ec4,0xbf55bec4,0xbf0ebf6d,
0x3f6d3f80,0xbec40000,0xbf6dbf80,0x3ec40000,0x3ec43f35,0xbf6dbf35,0xbec4bf35,0x3f6d3f35,0xbec40000,0xbf6dbf80,0x3ec40000,0x3f6d3f80,0xbf6dbf35,0xbec4bf35,0x3f6d3f35,0x3ec43f35,
0x3f7b3f80,0xbe480000,0xbe480000,0xbf7bbf80,0x3f553f6d,0xbf0ebec4,0xbf0ebec4,0xbf55bf6d,0x3f0e3f35,0xbf55bf35,0xbf55bf35,0xbf0ebf35,0x3e483ec4,0xbf7bbf6d,0xbf7bbf6d,0xbe48bec4,
0x3f803f80,0,0x3f803f80,0,0x3f803f80,0,0x3f803f80,0,0x3f803f80,0,0x3f803f80,0,0x3f803f80,0,0x3f803f80,0,
0xbf7bbf80,0xbe480000,0x3e480000,0xbf7bbf80,0xbf55bf6d,0xbf0ebec4,0x3f0e3ec4,0xbf55bf6d,0xbf0ebf35,0xbf55bf35,0x3f553f35,0xbf0ebf35,0xbe48bec4,0xbf7bbf6d,0x3f7b3f6d,0xbe48bec4,
0x3f6d3f80,0x3ec40000,0xbf6dbf80,0xbec40000,0x3ec43f35,0x3f6d3f35,0xbec4bf35,0xbf6dbf35,0xbec40000,0x3f6d3f80,0x3ec40000,0xbf6dbf80,0xbf6dbf35,0x3ec43f35,0x3f6d3f35,0xbec4bf35,
0xbf55bf80,0xbf0e0000,0xbf0e0000,0x3f553f80,0x3e48bec4,0xbf7bbf6d,0xbf7bbf6d,0xbe483ec4,0x3f7b3f35,0xbe48bf35,0xbe48bf35,0xbf7bbf35,0x3f0e3f6d,0x3f553ec4,0x3f553ec4,0xbf0ebf6d,
0x3f353f80,0x3f350000,0x3f353f80,0x3f350000,0xbf350000,0x3f353f80,0xbf350000,0x3f353f80,0xbf35bf80,0xbf350000,0xbf35bf80,0xbf350000,0x3f350000,0xbf35bf80,0x3f350000,0xbf35bf80,
0xbf0ebf80,0xbf550000,0x3f550000,0xbf0ebf80,0x3f7b3ec4,0xbe48bf6d,0x3e483f6d,0x3f7b3ec4,0xbe483f35,0x3f7b3f35,0xbf7bbf35,0xbe483f35,0xbf55bf6d,0xbf0e3ec4,0x3f0ebec4,0xbf55bf6d,
0x3ec43f80,0x3f6d0000,0xbec4bf80,0xbf6d0000,0xbf6dbf35,0xbec43f35,0x3f6d3f35,0x3ec4bf35,0x3f6d0000,0xbec4bf80,0xbf6d0000,0x3ec43f80,0xbec43f35,0x3f6d3f35,0x3ec4bf35,0xbf6dbf35,
0xbe48bf80,0xbf7b0000,0xbf7b0000,0x3e483f80,0x3f0e3f6d,0x3f55bec4,0x3f55bec4,0xbf0ebf6d,0xbf55bf35,0xbf0e3f35,0xbf0e3f35,0x3f553f35,0x3f7b3ec4,0x3e48bf6d,0x3e48bf6d,0xbf7bbec4,
0x3f80,0x3f800000,0x3f80,0x3f800000,0xbf80,0xbf800000,0xbf80,0xbf800000,0x3f80,0x3f800000,0x3f80,0x3f800000,0xbf80,0xbf800000,0xbf80,0xbf800000,
0x3e48bf80,0xbf7b0000,0x3f7b0000,0x3e48bf80,0xbf0e3f6d,0x3f553ec4,0xbf55bec4,0xbf0e3f6d,0x3f55bf35,0xbf0ebf35,0x3f0e3f35,0x3f55bf35,0xbf7b3ec4,0x3e483f6d,0xbe48bf6d,0xbf7b3ec4,
0xbec43f80,0x3f6d0000,0x3ec4bf80,0xbf6d0000,0x3f6dbf35,0xbec4bf35,0xbf6d3f35,0x3ec43f35,0xbf6d0000,0xbec43f80,0x3f6d0000,0x3ec4bf80,0x3ec43f35,0x3f6dbf35,0xbec4bf35,0xbf6d3f35,
0x3f0ebf80,0xbf550000,0xbf550000,0xbf0e3f80,0xbf7b3ec4,0xbe483f6d,0xbe483f6d,0x3f7bbec4,0x3e483f35,0x3f7bbf35,0x3f7bbf35,0xbe48bf35,0x3f55bf6d,0xbf0ebec4,0xbf0ebec4,0xbf553f6d,
0xbf353f80,0x3f350000,0xbf353f80,0x3f350000,0x3f350000,0x3f35bf80,0x3f350000,0x3f35bf80,0x3f35bf80,0xbf350000,0x3f35bf80,0xbf350000,0xbf350000,0xbf353f80,0xbf350000,0xbf353f80,
0x3f55bf80,0xbf0e0000,0x3f0e0000,0x3f55bf80,0xbe48bec4,0xbf7b3f6d,0x3f7bbf6d,0xbe48bec4,0xbf7b3f35,0xbe483f35,0x3e48bf35,0xbf7b3f35,0xbf0e3f6d,0x3f55bec4,0xbf553ec4,0xbf0e3f6d,
0xbf6d3f80,0x3ec40000,0x3f6dbf80,0xbec40000,0xbec43f35,0x3f6dbf35,0x3ec4bf35,0xbf6d3f35,0x3ec40000,0x3f6dbf80,0xbec40000,0xbf6d3f80,0x3f6dbf35,0x3ec4bf35,0xbf6d3f35,0xbec43f35,
0x3f7bbf80,0xbe480000,0xbe480000,0xbf7b3f80,0x3f55bf6d,0xbf0e3ec4,0xbf0e3ec4,0xbf553f6d,0x3f0ebf35,0xbf553f35,0xbf553f35,0xbf0e3f35,0x3e48bec4,0xbf7b3f6d,0xbf7b3f6d,0xbe483ec4,
0xbf803f80,0,0xbf803f80,0,0xbf803f80,0,0xbf803f80,0,0xbf803f80,0,0xbf803f80,0,0xbf803f80,0,0xbf803f80,0,
0x3f7bbf80,0x3e480000,0xbe480000,0x3f7bbf80,0x3f55bf6d,0x3f0ebec4,0xbf0e3ec4,0x3f55bf6d,0x3f0ebf35,0x3f55bf35,0xbf553f35,0x3f0ebf35,0x3e48bec4,0x3f7bbf6d,0xbf7b3f6d,0x3e48bec4,
0xbf6d3f80,0xbec40000,0x3f6dbf80,0x3ec40000,0xbec43f35,0xbf6d3f35,0x3ec4bf35,0x3f6dbf35,0x3ec40000,0xbf6d3f80,0xbec40000,0x3f6dbf80,0x3f6dbf35,0xbec43f35,0xbf6d3f35,0x3ec4bf35,
0x3f55bf80,0x3f0e0000,0x3f0e0000,0xbf553f80,0xbe48bec4,0x3f7bbf6d,0x3f7bbf6d,0x3e483ec4,0xbf7b3f35,0x3e48bf35,0x3e48bf35,0x3f7bbf35,0xbf0e3f6d,0xbf553ec4,0xbf553ec4,0x3f0ebf6d,
0xbf353f80,0xbf350000,0xbf353f80,0xbf350000,0x3f350000,0xbf353f80,0x3f350000,0xbf353f80,0x3f35bf80,0x3f350000,0x3f35bf80,0x3f350000,0xbf350000,0x3f35bf80,0xbf350000,0x3f35bf80,
0x3f0ebf80,0x3f550000,0xbf550000,0x3f0ebf80,0xbf7b3ec4,0x3e48bf6d,0xbe483f6d,0xbf7b3ec4,0x3e483f35,0xbf7b3f35,0x3f7bbf35,0x3e483f35,0x3f55bf6d,0x3f0e3ec4,0xbf0ebec4,0x3f55bf6d,
0xbec43f80,0xbf6d0000,0x3ec4bf80,0x3f6d0000,0x3f6dbf35,0x3ec43f35,0xbf6d3f35,0xbec4bf35,0xbf6d0000,0x3ec4bf80,0x3f6d0000,0xbec43f80,0x3ec43f35,0xbf6d3f35,0xbec4bf35,0x3f6dbf35,
0x3e48bf80,0x3f7b0000,0x3f7b0000,0xbe483f80,0xbf0e3f6d,0xbf55bec4,0xbf55bec4,0x3f0ebf6d,0x3f55bf35,0x3f0e3f35,0x3f0e3f35,0xbf553f35,0xbf7b3ec4,0xbe48bf6d,0xbe48bf6d,0x3f7bbec4,
0x3f80,0xbf800000,0x3f80,0xbf800000,0xbf80,0x3f800000,0xbf80,0x3f800000,0x3f80,0xbf800000,0x3f80,0xbf800000,0xbf80,0x3f800000,0xbf80,0x3f800000,
0xbe48bf80,0x3f7b0000,0xbf7b0000,0xbe48bf80,0x3f0e3f6d,0xbf553ec4,0x3f55bec4,0x3f0e3f6d,0xbf55bf35,0x3f0ebf35,0xbf0e3f35,0xbf55bf35,0x3f7b3ec4,0xbe483f6d,0x3e48bf6d,0x3f7b3ec4,
0x3ec43f80,0xbf6d0000,0xbec4bf80,0x3f6d0000,0xbf6dbf35,0x3ec4bf35,0x3f6d3f35,0xbec43f35,0x3f6d0000,0x3ec43f80,0xbf6d0000,0xbec4bf80,0xbec43f35,0xbf6dbf35,0x3ec4bf35,0x3f6d3f35,
0xbf0ebf80,0x3f550000,0x3f550000,0x3f0e3f80,0x3f7b3ec4,0x3e483f6d,0x3e483f6d,0xbf7bbec4,0xbe483f35,0xbf7bbf35,0xbf7bbf35,0x3e48bf35,0xbf55bf6d,0x3f0ebec4,0x3f0ebec4,0x3f553f6d,
0x3f353f80,0xbf350000,0x3f353f80,0xbf350000,0xbf350000,0xbf35bf80,0xbf350000,0xbf35bf80,0xbf35bf80,0x3f350000,0xbf35bf80,0x3f350000,0x3f350000,0x3f353f80,0x3f350000,0x3f353f80,
0xbf55bf80,0x3f0e0000,0xbf0e0000,0xbf55bf80,0x3e48bec4,0x3f7b3f6d,0xbf7bbf6d,0x3e48bec4,0x3f7b3f35,0x3e483f35,0xbe48bf35,0x3f7b3f35,0x3f0e3f6d,0xbf55bec4,0x3f553ec4,0x3f0e3f6d,
0x3f6d3f80,0xbec40000,0xbf6dbf80,0x3ec40000,0x3ec43f35,0xbf6dbf35,0xbec4bf35,0x3f6d3f35,0xbec40000,0xbf6dbf80,0x3ec40000,0x3f6d3f80,0xbf6dbf35,0xbec4bf35,0x3f6d3f35,0x3ec43f35,
0xbf7bbf80,0x3e480000,0x3e480000,0x3f7b3f80,0xbf55bf6d,0x3f0e3ec4,0x3f0e3ec4,0x3f553f6d,0xbf0ebf35,0x3f553f35,0x3f553f35,0x3f0e3f35,0xbe48bec4,0x3f7b3f6d,0x3f7b3f6d,0x3e483ec4,
0x80008000,0x3f803f80,0x80008000,0x3f803f80,0x80008000,0x3f803f80,0x80008000,0x3f803f80,0x80008000,0x3f803f80,0x80008000,0x3f803f80,0x80008000,0x3f803f80,0x80008000,0x3f803f80,
0xbe488000,0x3f7b3f80,0xbf7bbf80,0xbe480000,0xbf0ebec4,0x3f553f6d,0xbf55bf6d,0xbf0ebec4,0xbf55bf35,0x3f0e3f35,0xbf0ebf35,0xbf55bf35,0xbf7bbf6d,0x3e483ec4,0xbe48bec4,0xbf7bbf6d,
0xbec48000,0x3f6d3f80,0x3ec48000,0xbf6dbf80,0xbf6dbf35,0x3ec43f35,0x3f6d3f35,0xbec4bf35,0xbf6dbf80,0xbec40000,0x3f6d3f80,0x3ec40000,0xbec4bf35,0xbf6dbf35,0x3ec43f35,0x3f6d3f35,
0xbf0e8000,0x3f553f80,0x3f553f80,0x3f0e0000,0xbf7bbf6d,0xbe483ec4,0xbe483ec4,0x3f7b3f6d,0xbe48bf35,0xbf7bbf35,0xbf7bbf35,0x3e483f35,0x3f553ec4,0xbf0ebf6d,0xbf0ebf6d,0xbf55bec4,
0xbf358000,0x3f353f80,0xbf358000,0x3f353f80,0xbf35bf80,0xbf350000,0xbf35bf80,0xbf350000,0x3f358000,0xbf35bf80,0x3f358000,0xbf35bf80,0x3f353f80,0x3f350000,0x3f353f80,0x3f350000,
0xbf558000,0x3f0e3f80,0xbf0ebf80,0xbf550000,0xbe48bf6d,0xbf7bbec4,0x3f7b3ec4,0xbe48bf6d,0x3f7b3f35,0x3e48bf35,0xbe483f35,0x3f7b3f35,0xbf0e3ec4,0x3f553f6d,0xbf55bf6d,0xbf0e3ec4,
0xbf6d8000,0x3ec43f80,0x3f6d8000,0xbec4bf80,0x3ec4bf35,0xbf6dbf35,0xbec43f35,0x3f6d3f35,0x3ec43f80,0x3f6d0000,0xbec4bf80,0xbf6d0000,0xbf6dbf35,0xbec43f35,0x3f6d3f35,0x3ec4bf35,
0xbf7b8000,0x3e483f80,0x3e483f80,0x3f7b0000,0x3f55bec4,0xbf0ebf6d,0xbf0ebf6d,0xbf553ec4,0xbf0e3f35,0x3f553f35,0x3f553f35,0x3f0ebf35,0x3e48bf6d,0xbf7bbec4,0xbf7bbec4,0xbe483f6d,
0xbf808000,0x3f80,0xbf808000,0x3f80,0x3f808000,0xbf80,0x3f808000,0xbf80,0xbf808000,0x3f80,0xbf808000,0x3f80,0x3f808000,0xbf80,0x3f808000,0xbf80,
0xbf7b8000,0xbe483f80,0x3e48bf80,0xbf7b0000,0x3f553ec4,0x3f0ebf6d,0xbf0e3f6d,0x3f553ec4,0xbf0ebf35,0xbf553f35,0x3f55bf35,0xbf0ebf35,0x3e483f6d,0x3f7bbec4,0xbf7b3ec4,0x3e483f6d,
0xbf6d8000,0xbec43f80,0x3f6d8000,0x3ec4bf80,0x3ec43f35,0x3f6dbf35,0xbec4bf35,0xbf6d3f35,0x3ec4bf80,0xbf6d0000,0xbec43f80,0x3f6d0000,0xbf6d3f35,0x3ec43f35,0x3f6dbf35,0xbec4bf35,
0xbf558000,0xbf0e3f80,0xbf0e3f80,0x3f550000,0xbe483f6d,0x3f7bbec4,0x3f7bbec4,0x3e48bf6d,0x3f7bbf35,0xbe48bf35,0xbe48bf35,0xbf7b3f35,0xbf0ebec4,0xbf553f6d,0xbf553f6d,0x3f0e3ec4,
0xbf358000,0xbf353f80,0xbf358000,0xbf353f80,0xbf353f80,0x3f350000,0xbf353f80,0x3f350000,0x3f358000,0x3f35bf80,0x3f358000,0x3f35bf80,0x3f35bf80,0xbf350000,0x3f35bf80,0xbf350000,
0xbf0e8000,0xbf553f80,0x3f55bf80,0xbf0e0000,0xbf7b3f6d,0x3e483ec4,0xbe48bec4,0xbf7b3f6d,0xbe483f35,0x3f7bbf35,0xbf7b3f35,0xbe483f35,0x3f55bec4,0x3f0ebf6d,0xbf0e3f6d,0x3f55bec4,
0xbec48000,0xbf6d3f80,0x3ec48000,0x3f6dbf80,0xbf6d3f35,0xbec43f35,0x3f6dbf35,0x3ec4bf35,0xbf6d3f80,0x3ec40000,0x3f6dbf80,0xbec40000,0xbec43f35,0x3f6dbf35,0x3ec4bf35,0xbf6d3f35,
0xbe488000,0xbf7b3f80,0xbf7b3f80,0x3e480000,0xbf0e3ec4,0xbf553f6d,0xbf553f6d,0x3f0ebec4,0xbf553f35,0xbf0e3f35,0xbf0e3f35,0x3f55bf35,0xbf7b3f6d,0xbe483ec4,0xbe483ec4,0x3f7bbf6d,
0x80008000,0xbf803f80,0x80008000,0xbf803f80,0x80008000,0xbf803f80,0x80008000,0xbf803f80,0x80008000,0xbf803f80,0x80008000,0xbf803f80,0x80008000,0xbf803f80,0x80008000,0xbf803f80,
0x3e488000,0xbf7b3f80,0x3f7bbf80,0x3e480000,0x3f0ebec4,0xbf553f6d,0x3f55bf6d,0x3f0ebec4,0x3f55bf35,0xbf0e3f35,0x3f0ebf35,0x3f55bf35,0x3f7bbf6d,0xbe483ec4,0x3e48bec4,0x3f7bbf6d,
0x3ec48000,0xbf6d3f80,0xbec48000,0x3f6dbf80,0x3f6dbf35,0xbec43f35,0xbf6d3f35,0x3ec4bf35,0x3f6dbf80,0x3ec40000,0xbf6d3f80,0xbec40000,0x3ec4bf35,0x3f6dbf35,0xbec43f35,0xbf6d3f35,
0x3f0e8000,0xbf553f80,0xbf553f80,0xbf0e0000,0x3f7bbf6d,0x3e483ec4,0x3e483ec4,0xbf7b3f6d,0x3e48bf35,0x3f7bbf35,0x3f7bbf35,0xbe483f35,0xbf553ec4,0x3f0ebf6d,0x3f0ebf6d,0x3f55bec4,
0x3f358000,0xbf353f80,0x3f358000,0xbf353f80,0x3f35bf80,0x3f350000,0x3f35bf80,0x3f350000,0xbf358000,0x3f35bf80,0xbf358000,0x3f35bf80,0xbf353f80,0xbf350000,0xbf353f80,0xbf350000,
0x3f558000,0xbf0e3f80,0x3f0ebf80,0x3f550000,0x3e48bf6d,0x3f7bbec4,0xbf7b3ec4,0x3e48bf6d,0xbf7b3f35,0xbe48bf35,0x3e483f35,0xbf7b3f35,0x3f0e3ec4,0xbf553f6d,0x3f55bf6d,0x3f0e3ec4,
0x3f6d8000,0xbec43f80,0xbf6d8000,0x3ec4bf80,0xbec4bf35,0x3f6dbf35,0x3ec43f35,0xbf6d3f35,0xbec43f80,0xbf6d0000,0x3ec4bf80,0x3f6d0000,0x3f6dbf35,0x3ec43f35,0xbf6d3f35,0xbec4bf35,
0x3f7b8000,0xbe483f80,0xbe483f80,0xbf7b0000,0xbf55bec4,0x3f0ebf6d,0x3f0ebf6d,0x3f553ec4,0x3f0e3f35,0xbf553f35,0xbf553f35,0xbf0ebf35,0xbe48bf6d,0x3f7bbec4,0x3f7bbec4,0x3e483f6d,
0x3f808000,0x3f80,0x3f808000,0x3f80,0xbf808000,0xbf80,0xbf808000,0xbf80,0x3f808000,0x3f80,0x3f808000,0x3f80,0xbf808000,0xbf80,0xbf808000,0xbf80,
0x3f7b8000,0x3e483f80,0xbe48bf80,0x3f7b0000,0xbf553ec4,0xbf0ebf6d,0x3f0e3f6d,0xbf553ec4,0x3f0ebf35,0x3f553f35,0xbf55bf35,0x3f0ebf35,0xbe483f6d,0xbf7bbec4,0x3f7b3ec4,0xbe483f6d,
0x3f6d8000,0x3ec43f80,0xbf6d8000,0xbec4bf80,0xbec43f35,0xbf6dbf35,0x3ec4bf35,0x3f6d3f35,0xbec4bf80,0x3f6d0000,0x3ec43f80,0xbf6d0000,0x3f6d3f35,0xbec43f35,0xbf6dbf35,0x3ec4bf35,
0x3f558000,0x3f0e3f80,0x3f0e3f80,0xbf550000,0x3e483f6d,0xbf7bbec4,0xbf7bbec4,0xbe48bf6d,0xbf7bbf35,0x3e48bf35,0x3e48bf35,0x3f7b3f35,0x3f0ebec4,0x3f553f6d,0x3f553f6d,0xbf0e3ec4,
0x3f358000,0x3f353f80,0x3f358000,0x3f353f80,0x3f353f80,0xbf350000,0x3f353f80,0xbf350000,0xbf358000,0xbf35bf80,0xbf358000,0xbf35bf80,0xbf35bf80,0x3f350000,0xbf35bf80,0x3f350000,
0x3f0e8000,0x3f553f80,0xbf55bf80,0x3f0e0000,0x3f7b3f6d,0xbe483ec4,0x3e48bec4,0x3f7b3f6d,0x3e483f35,0xbf7bbf35,0x3f7b3f35,0x3e483f35,0xbf55bec4,0xbf0ebf6d,0x3f0e3f6d,0xbf55bec4,
0x3ec48000,0x3f6d3f80,0xbec48000,0xbf6dbf80,0x3f6d3f35,0x3ec43f35,0xbf6dbf35,0xbec4bf35,0x3f6d3f80,0xbec40000,0xbf6dbf80,0x3ec40000,0x3ec43f35,0xbf6dbf35,0xbec4bf35,0x3f6d3f35,
0x3e488000,0x3f7b3f80,0x3f7b3f80,0xbe480000,0x3f0e3ec4,0x3f553f6d,0x3f553f6d,0xbf0ebec4,0x3f553f35,0x3f0e3f35,0x3f0e3f35,0xbf55bf35,0x3f7b3f6d,0x3e483ec4,0x3e483ec4,0xbf7bbf6d,
0x80008000,0x3f803f80,0x80008000,0x3f803f80,0x80008000,0x3f803f80,0x80008000,0x3f803f80,0x80008000,0x3f803f80,0x80008000,0x3f803f80,0x80008000,0x3f803f80,0x80008000,0x3f803f80,
0x3e488000,0xbf7bbf80,0x3f7b3f80,0x3e480000,0x3f0e3ec4,0xbf55bf6d,0x3f553f6d,0x3f0e3ec4,0x3f553f35,0xbf0ebf35,0x3f0e3f35,0x3f553f35,0x3f7b3f6d,0xbe48bec4,0x3e483ec4,0x3f7b3f6d,
0xbec48000,0x3f6d3f80,0x3ec48000,0xbf6dbf80,0xbf6dbf35,0x3ec43f35,0x3f6d3f35,0xbec4bf35,0xbf6dbf80,0xbec40000,0x3f6d3f80,0x3ec40000,0xbec4bf35,0xbf6dbf35,0x3ec43f35,0x3f6d3f35,
0x3f0e8000,0xbf55bf80,0xbf55bf80,0xbf0e0000,0x3f7b3f6d,0x3e48bec4,0x3e48bec4,0xbf7bbf6d,0x3e483f35,0x3f7b3f35,0x3f7b3f35,0xbe48bf35,0xbf55bec4,0x3f0e3f6d,0x3f0e3f6d,0x3f553ec4,
0xbf358000,0x3f353f80,0xbf358000,0x3f353f80,0xbf35bf80,0xbf350000,0xbf35bf80,0xbf350000,0x3f358000,0xbf35bf80,0x3f358000,0xbf35bf80,0x3f353f80,0x3f350000,0x3f353f80,0x3f350000,
0x3f558000,0xbf0ebf80,0x3f0e3f80,0x3f550000,0x3e483f6d,0x3f7b3ec4,0xbf7bbec4,0x3e483f6d,0xbf7bbf35,0xbe483f35,0x3e48bf35,0xbf7bbf35,0x3f0ebec4,0xbf55bf6d,0x3f553f6d,0x3f0ebec4,
0xbf6d8000,0x3ec43f80,0x3f6d8000,0xbec4bf80,0x3ec4bf35,0xbf6dbf35,0xbec43f35,0x3f6d3f35,0x3ec43f80,0x3f6d0000,0xbec4bf80,0xbf6d0000,0xbf6dbf35,0xbec43f35,0x3f6d3f35,0x3ec4bf35,
0x3f7b8000,0xbe48bf80,0xbe48bf80,0xbf7b0000,0xbf553ec4,0x3f0e3f6d,0x3f0e3f6d,0x3f55bec4,0x3f0ebf35,0xbf55bf35,0xbf55bf35,0xbf0e3f35,0xbe483f6d,0x3f7b3ec4,0x3f7b3ec4,0x3e48bf6d,
0xbf808000,0x3f80,0xbf808000,0x3f80,0x3f808000,0xbf80,0x3f808000,0xbf80,0xbf808000,0x3f80,0xbf808000,0x3f80,0x3f808000,0xbf80,0x3f808000,0xbf80,
0x3f7b8000,0x3e48bf80,0xbe483f80,0x3f7b0000,0xbf55bec4,0xbf0e3f6d,0x3f0ebf6d,0xbf55bec4,0x3f0e3f35,0x3f55bf35,0xbf553f35,0x3f0e3f35,0xbe48bf6d,0xbf7b3ec4,0x3f7bbec4,0xbe48bf6d,
0xbf6d8000,0xbec43f80,0x3f6d8000,0x3ec4bf80,0x3ec43f35,0x3f6dbf35,0xbec4bf35,0xbf6d3f35,0x3ec4bf80,0xbf6d0000,0xbec43f80,0x3f6d0000,0xbf6d3f35,0x3ec43f35,0x3f6dbf35,0xbec4bf35,
0x3f558000,0x3f0ebf80,0x3f0ebf80,0xbf550000,0x3e48bf6d,0xbf7b3ec4,0xbf7b3ec4,0xbe483f6d,0xbf7b3f35,0x3e483f35,0x3e483f35,0x3f7bbf35,0x3f0e3ec4,0x3f55bf6d,0x3f55bf6d,0xbf0ebec4,
0xbf358000,0xbf353f80,0xbf358000,0xbf353f80,0xbf353f80,0x3f350000,0xbf353f80,0x3f350000,0x3f358000,0x3f35bf80,0x3f358000,0x3f35bf80,0x3f35bf80,0xbf350000,0x3f35bf80,0xbf350000,
0x3f0e8000,0x3f55bf80,0xbf553f80,0x3f0e0000,0x3f7bbf6d,0xbe48bec4,0x3e483ec4,0x3f7bbf6d,0x3e48bf35,0xbf7b3f35,0x3f7bbf35,0x3e48bf35,0xbf553ec4,0xbf0e3f6d,0x3f0ebf6d,0xbf553ec4,
0xbec48000,0xbf6d3f80,0x3ec48000,0x3f6dbf80,0xbf6d3f35,0xbec43f35,0x3f6dbf35,0x3ec4bf35,0xbf6d3f80,0x3ec40000,0x3f6dbf80,0xbec40000,0xbec43f35,0x3f6dbf35,0x3ec4bf35,0xbf6d3f35,
0x3e488000,0x3f7bbf80,0x3f7bbf80,0xbe480000,0x3f0ebec4,0x3f55bf6d,0x3f55bf6d,0xbf0e3ec4,0x3f55bf35,0x3f0ebf35,0x3f0ebf35,0xbf553f35,0x3f7bbf6d,0x3e48bec4,0x3e48bec4,0xbf7b3f6d,
0x80008000,0xbf803f80,0x80008000,0xbf803f80,0x80008000,0xbf803f80,0x80008000,0xbf803f80,0x80008000,0xbf803f80,0x80008000,0xbf803f80,0x80008000,0xbf803f80,0x80008000,0xbf803f80,
0xbe488000,0x3f7bbf80,0xbf7b3f80,0xbe480000,0xbf0e3ec4,0x3f55bf6d,0xbf553f6d,0xbf0e3ec4,0xbf553f35,0x3f0ebf35,0xbf0e3f35,0xbf553f35,0xbf7b3f6d,0x3e48bec4,0xbe483ec4,0xbf7b3f6d,
0x3ec48000,0xbf6d3f80,0xbec48000,0x3f6dbf80,0x3f6dbf35,0xbec43f35,0xbf6d3f35,0x3ec4bf35,0x3f6dbf80,0x3ec40000,0xbf6d3f80,0xbec40000,0x3ec4bf35,0x3f6dbf35,0xbec43f35,0xbf6d3f35,
0xbf0e8000,0x3f55bf80,0x3f55bf80,0x3f0e0000,0xbf7b3f6d,0xbe48bec4,0xbe48bec4,0x3f7bbf6d,0xbe483f35,0xbf7b3f35,0xbf7b3f35,0x3e48bf35,0x3f55bec4,0xbf0e3f6d,0xbf0e3f6d,0xbf553ec4,
0x3f358000,0xbf353f80,0x3f358000,0xbf353f80,0x3f35bf80,0x3f350000,0x3f35bf80,0x3f350000,0xbf358000,0x3f35bf80,0xbf358000,0x3f35bf80,0xbf353f80,0xbf350000,0xbf353f80,0xbf350000,
0xbf558000,0x3f0ebf80,0xbf0e3f80,0xbf550000,0xbe483f6d,0xbf7b3ec4,0x3f7bbec4,0xbe483f6d,0x3f7bbf35,0x3e483f35,0xbe48bf35,0x3f7bbf35,0xbf0ebec4,0x3f55bf6d,0xbf553f6d,0xbf0ebec4,
0x3f6d8000,0xbec43f80,0xbf6d8000,0x3ec4bf80,0xbec4bf35,0x3f6dbf35,0x3ec43f35,0xbf6d3f35,0xbec43f80,0xbf6d0000,0x3ec4bf80,0x3f6d0000,0x3f6dbf35,0x3ec43f35,0xbf6d3f35,0xbec4bf35,
0xbf7b8000,0x3e48bf80,0x3e48bf80,0x3f7b0000,0x3f553ec4,0xbf0e3f6d,0xbf0e3f6d,0xbf55bec4,0xbf0ebf35,0x3f55bf35,0x3f55bf35,0x3f0e3f35,0x3e483f6d,0xbf7b3ec4,0xbf7b3ec4,0xbe48bf6d,
0x3f808000,0x3f80,0x3f808000,0x3f80,0xbf808000,0xbf80,0xbf808000,0xbf80,0x3f808000,0x3f80,0x3f808000,0x3f80,0xbf808000,0xbf80,0xbf808000,0xbf80,
0xbf7b8000,0xbe48bf80,0x3e483f80,0xbf7b0000,0x3f55bec4,0x3f0e3f6d,0xbf0ebf6d,0x3f55bec4,0xbf0e3f35,0xbf55bf35,0x3f553f35,0xbf0e3f35,0x3e48bf6d,0x3f7b3ec4,0xbf7bbec4,0x3e48bf6d,
0x3f6d8000,0x3ec43f80,0xbf6d8000,0xbec4bf80,0xbec43f35,0xbf6dbf35,0x3ec4bf35,0x3f6d3f35,0xbec4bf80,0x3f6d0000,0x3ec43f80,0xbf6d0000,0x3f6d3f35,0xbec43f35,0xbf6dbf35,0x3ec4bf35,
0xbf558000,0xbf0ebf80,0xbf0ebf80,0x3f550000,0xbe48bf6d,0x3f7b3ec4,0x3f7b3ec4,0x3e483f6d,0x3f7b3f35,0xbe483f35,0xbe483f35,0xbf7bbf35,0xbf0e3ec4,0xbf55bf6d,0xbf55bf6d,0x3f0ebec4,
0x3f358000,0x3f353f80,0x3f358000,0x3f353f80,0x3f353f80,0xbf350000,0x3f353f80,0xbf350000,0xbf358000,0xbf35bf80,0xbf358000,0xbf35bf80,0xbf35bf80,0x3f350000,0xbf35bf80,0x3f350000,
0xbf0e8000,0xbf55bf80,0x3f553f80,0xbf0e0000,0xbf7bbf6d,0x3e48bec4,0xbe483ec4,0xbf7bbf6d,0xbe48bf35,0x3f7b3f35,0xbf7bbf35,0xbe48bf35,0x3f553ec4,0x3f0e3f6d,0xbf0ebf6d,0x3f553ec4,
0x3ec48000,0x3f6d3f80,0xbec48000,0xbf6dbf80,0x3f6d3f35,0x3ec43f35,0xbf6dbf35,0xbec4bf35,0x3f6d3f80,0xbec40000,0xbf6dbf80,0x3ec40000,0x3ec43f35,0xbf6dbf35,0xbec4bf35,0x3f6d3f35,
0xbe488000,0xbf7bbf80,0xbf7bbf80,0x3e480000,0xbf0ebec4,0xbf55bf6d,0xbf55bf6d,0x3f0e3ec4,0xbf55bf35,0xbf0ebf35,0xbf0ebf35,0x3f553f35,0xbf7bbf6d,0xbe48bec4,0xbe48bec4,0x3f7b3f6d};
__device__ __align__(128) const uint32_t c_smt[8704] = {
0x3c003c00,0x3c003c00,0x3c003c00,0x3c003c00,0x3b643c00,0x361f39a8,0xb61f0000,0xbb64b9a8,0x39a83c00,0xb9a80000,0xb9a8bc00,0x39a80000,0x361f3c00,0xbb64b9a8,0x3b640000,0xb61f39a8,
0x3c00,0xbc00,0x3c00,0xbc00,0xb61f3c00,0x3b64b9a8,0xbb640000,0x361f39a8,0xb9a83c00,0x39a80000,0x39a8bc00,0xb9a80000,0xbb643c00,0xb61f39a8,0x361f0000,0x3b64b9a8,
0x3c003c00,0x3c003c00,0x3c003c00,0x3c003c00,0xbb64bc00,0xb61fb9a8,0x361f0000,0x3b6439a8,0x39a83c00,0xb9a80000,0xb9a8bc00,0x39a80000,0xb61fbc00,0x3b6439a8,0xbb640000,0x361fb9a8,
0x3c00,0xbc00,0x3c00,0xbc00,0x361fbc00,0xbb6439a8,0x3b640000,0xb61fb9a8,0xb9a83c00,0x39a80000,0x39a8bc00,0xb9a80000,0x3b64bc00,0x361fb9a8,0xb61f0000,0xbb6439a8,
0xbc003c00,0xbc003c00,0xbc003c00,0xbc003c00,0xbb643c00,0xb61f39a8,0x361f0000,0x3b64b9a8,0xb9a83c00,0x39a80000,0x39a8bc00,0xb9a80000,0xb61f3c00,0x3b64b9a8,0xbb640000,0x361f39a8,
0x3c00,0xbc00,0x3c00,0xbc00,0x361f3c00,0xbb64b9a8,0x3b640000,0xb61f39a8,0x39a83c00,0xb9a80000,0xb9a8bc00,0x39a80000,0x3b643c00,0x361f39a8,0xb61f0000,0xbb64b9a8,
0xbc003c00,0xbc003c00,0xbc003c00,0xbc003c00,0x3b64bc00,0x361fb9a8,0xb61f0000,0xbb6439a8,0xb9a83c00,0x39a80000,0x39a8bc00,0xb9a80000,0x361fbc00,0xbb6439a8,0x3b640000,0xb61fb9a8,
0x3c00,0xbc00,0x3c00,0xbc00,0xb61fbc00,0x3b6439a8,0xbb640000,0x361fb9a8,0x39a83c00,0xb9a80000,0xb9a8bc00,0x39a80000,0xbb64bc00,0xb61fb9a8,0x361f0000,0x3b6439a8,
0,0,0,0,0x361f0000,0x3b6439a8,0x3b643c00,0x361f39a8,0x39a80000,0x39a83c00,0xb9a80000,0xb9a8bc00,0x3b640000,0xb61f39a8,0xb61fbc00,0x3b6439a8,
0x3c000000,0xbc000000,0x3c000000,0xbc000000,0x3b640000,0xb61fb9a8,0xb61f3c00,0x3b64b9a8,0x39a80000,0x39a8bc00,0xb9a80000,0xb9a83c00,0x361f0000,0x3b64b9a8,0x3b64bc00,0x361fb9a8,
0,0,0,0,0xb61f0000,0xbb64b9a8,0xbb64bc00,0xb61fb9a8,0x39a80000,0x39a83c00,0xb9a80000,0xb9a8bc00,0xbb640000,0x361fb9a8,0x361f3c00,0xbb64b9a8,
0x3c000000,0xbc000000,0x3c000000,0xbc000000,0xbb640000,0x361f39a8,0x361fbc00,0xbb6439a8,0x39a80000,0x39a8bc00,0xb9a80000,0xb9a83c00,0xb61f0000,0xbb6439a8,0xbb643c00,0xb61f39a8,
0,0,0,0,0xb61f0000,0xbb6439a8,0xbb643c00,0xb61f39a8,0xb9a80000,0xb9a83c00,0x39a80000,0x39a8bc00,0xbb640000,0x361f39a8,0x361fbc00,0xbb6439a8,
0xbc000000,0x3c000000,0xbc000000,0x3c000000,0xbb640000,0x361fb9a8,0x361f3c00,0xbb64b9a8,0xb9a80000,0xb9a8bc00,0x39a80000,0x39a83c00,0xb61f0000,0xbb64b9a8,0xbb64bc00,0xb61fb9a8,
0,0,0,0,0x361f0000,0x3b64b9a8,0x3b64bc00,0x361fb9a8,0xb9a80000,0xb9a83c00,0x39a80000,0x39a8bc00,0x3b640000,0xb61fb9a8,0xb61f3c00,0x3b64b9a8,
0xbc000000,0x3c000000,0xbc000000,0x3c000000,0x3b640000,0xb61f39a8,0xb61fbc00,0x3b6439a8,0xb9a80000,0xb9a8bc00,0x39a80000,0x39a83c00,0x361f0000,0x3b6439a8,0x3b643c00,0x361f39a8,
0x3f803f80,0x3f803f80,0x3f803f80,0x3f803f80,0x3f6d3f80,0x3ec43f35,0xbec40000,0xbf6dbf35,0x3f353f80,0xbf350000,0xbf35bf80,0x3f350000,0x3ec43f80,0xbf6dbf35,0x3f6d0000,0xbec43f35,
0x3f80,0xbf80,0x3f80,0xbf80,0xbec43f80,0x3f6dbf35,0xbf6d0000,0x3ec43f35,0xbf353f80,0x3f350000,0x3f35bf80,0xbf350000,0xbf6d3f80,0xbec43f35,0x3ec40000,0x3f6dbf35,
0x3f803f80,0x3f803f80,0x3f803f80,0x3f803f80,0xbf6dbf80,0xbec4bf35,0x3ec40000,0x3f6d3f35,0x3f353f80,0xbf350000,0xbf35bf80,0x3f350000,0xbec4bf80,0x3f6d3f35,0xbf6d0000,0x3ec4bf35,
0x3f80,0xbf80,0x3f80,0xbf80,0x3ec4bf80,0xbf6d3f35,0x3f6d0000,0xbec4bf35,0xbf353f80,0x3f350000,0x3f35bf80,0xbf350000,0x3f6dbf80,0x3ec4bf35,0xbec40000,0xbf6d3f35,
0xbf803f80,0xbf803f80,0xbf803f80,0xbf803f80,0xbf6d3f80,0xbec43f35,0x3ec40000,0x3f6dbf35,0xbf353f80,0x3f350000,0x3f35bf80,0xbf350000,0xbec43f80,0x3f6dbf35,0xbf6d0000,0x3ec43f35,
0x3f80,0xbf80,0x3f80,0xbf80,0x3ec43f80,0xbf6dbf35,0x3f6d0000,0xbec43f35,0x3f353f80,0xbf350000,0xbf35bf80,0x3f350000,0x3f6d3f80,0x3ec43f35,0xbec40000,0xbf6dbf35,
0xbf803f80,0xbf803f80,0xbf803f80,0xbf803f80,0x3f6dbf80,0x3ec4bf35,0xbec40000,0xbf6d3f35,0xbf353f80,0x3f350000,0x3f35bf80,0xbf350000,0x3ec4bf80,0xbf6d3f35,0x3f6d0000,0xbec4bf35,
0x3f80,0xbf80,0x3f80,0xbf80,0xbec4bf80,0x3f6d3f35,0xbf6d0000,0x3ec4bf35,0x3f353f80,0xbf350000,0xbf35bf80,0x3f350000,0xbf6dbf80,0xbec4bf35,0x3ec40000,0x3f6d3f35,
0,0,0,0,0x3ec40000,0x3f6d3f35,0x3f6d3f80,0x3ec43f35,0x3f350000,0x3f353f80,0xbf350000,0xbf35bf80,0x3f6d0000,0xbec43f35,0xbec4bf80,0x3f6d3f35,
0x3f800000,0xbf800000,0x3f800000,0xbf800000,0x3f6d0000,0xbec4bf35,0xbec43f80,0x3f6dbf35,0x3f350000,0x3f35bf80,0xbf350000,0xbf353f80,0x3ec40000,0x3f6dbf35,0x3f6dbf80,0x3ec4bf35,
0,0,0,0,0xbec40000,0xbf6dbf35,0xbf6dbf80,0xbec4bf35,0x3f350000,0x3f353f80,0xbf350000,0xbf35bf80,0xbf6d0000,0x3ec4bf35,0x3ec43f80,0xbf6dbf35,
0x3f800000,0xbf800000,0x3f800000,0xbf800000,0xbf6d0000,0x3ec43f35,0x3ec4bf80,0xbf6d3f35,0x3f350000,0x3f35bf80,0xbf350000,0xbf353f80,0xbec40000,0xbf6d3f35,0xbf6d3f80,0xbec43f35,
0,0,0,0,0xbec40000,0xbf6d3f35,0xbf6d3f80,0xbec43f35,0xbf350000,0xbf353f80,0x3f350000,0x3f35bf80,0xbf6d0000,0x3ec43f35,0x3ec4bf80,0xbf6d3f35,
0xbf800000,0x3f800000,0xbf800000,0x3f800000,0xbf6d0000,0x3ec4bf35,0x3ec43f80,0xbf6dbf35,0xbf350000,0xbf35bf80,0x3f350000,0x3f353f80,0xbec40000,0xbf6dbf35,0xbf6dbf80,0xbec4bf35,
0,0,0,0,0x3ec40000,0x3f6dbf35,0x3f6dbf80,0x3ec4bf35,0xbf350000,0xbf353f80,0x3f350000,0x3f35bf80,0x3f6d0000,0xbec4bf35,0xbec43f80,0x3f6dbf35,
0xbf800000,0x3f800000,0xbf800000,0x3f800000,0x3f6d0000,0xbec43f35,0xbec4bf80,0x3f6d3f35,0xbf350000,0xbf35bf80,0x3f350000,0x3f353f80,0x3ec40000,0x3f6d3f35,0x3f6d3f80,0x3ec43f35,
0x3c003c00,0x3c003c00,0x3c003c00,0x3c003c00,0x3bf63c00,0x3ba83bd9,0x3b0e3b64,0x3a2f3aa7,0x3bd93c00,0x3aa73b64,0x387239a8,0x323e361f,0x3ba83c00,0x39133aa7,0x2e46361f,0xb78bb23e,
0x3b643c00,0x361f39a8,0xb61f0000,0xbb64b9a8,0x3b0e3c00,0x2e463872,0xba2fb61f,0xbba8bbd9,0x3aa73c00,0xb23e361f,0xbbd9b9a8,0xb872bb64,0x3a2f3c00,0xb78b323e,0xbba8bb64,0x2e46b872,
0x39a83c00,0xb9a80000,0xb9a8bc00,0x39a80000,0x39133c00,0xbb0eb23e,0xb4a5bb64,0x3bf63872,0x38723c00,0xbbd9b61f,0x323eb9a8,0x3aa73b64,0x378b3c00,0xbbf6b872,0x3913b61f,0x34a53bd9,
0x361f3c00,0xbb64b9a8,0x3b640000,0xb61f39a8,0x34a53c00,0xba2fbaa7,0x3bf6361f,0xbb0e323e,0x323e3c00,0xb872bb64,0x3aa739a8,0xbbd9b61f,0x2e463c00,0xb4a5bbd9,0x378b3b64,0xb913baa7,
0x3c00,0xbc00,0x3c00,0xbc00,0xae463c00,0x34a5bbd9,0xb78b3b64,0x3913baa7,0xb23e3c00,0x3872bb64,0xbaa739a8,0x3bd9b61f,0xb4a53c00,0x3a2fbaa7,0xbbf6361f,0x3b0e323e,
0xb61f3c00,0x3b64b9a8,0xbb640000,0x361f39a8,0xb78b3c00,0x3bf6b872,0xb913b61f,0xb4a53bd9,0xb8723c00,0x3bd9b61f,0xb23eb9a8,0xbaa73b64,0xb9133c00,0x3b0eb23e,0x34a5bb64,0xbbf63872,
0xb9a83c00,0x39a80000,0x39a8bc00,0xb9a80000,0xba2f3c00,0x378b323e,0x3ba8bb64,0xae46b872,0xbaa73c00,0x323e361f,0x3bd9b9a8,0x3872bb64,0xbb0e3c00,0xae463872,0x3a2fb61f,0x3ba8bbd9,
0xbb643c00,0xb61f39a8,0x361f0000,0x3b64b9a8,0xbba83c00,0xb9133aa7,0xae46361f,0x378bb23e,0xbbd93c00,0xbaa73b64,0xb87239a8,0xb23e361f,0xbbf63c00,0xbba83bd9,0xbb0e3b64,0xba2f3aa7,
0xbc003c00,0xbc003c00,0xbc003c00,0xbc003c00,0xbbf63c00,0xbba83bd9,0xbb0e3b64,0xba2f3aa7,0xbbd93c00,0xbaa73b64,0xb87239a8,0xb23e361f,0xbba83c00,0xb9133aa7,0xae46361f,0x378bb23e,
0xbb643c00,0xb61f39a8,0x361f0000,0x3b64b9a8,0xbb0e3c00,0xae463872,0x3a2fb61f,0x3ba8bbd9,0xbaa73c00,0x323e361f,0x3bd9b9a8,0x3872bb64,0xba2f3c00,0x378b323e,0x3ba8bb64,0xae46b872,
0xb9a83c00,0x39a80000,0x39a8bc00,0xb9a80000,0xb9133c00,0x3b0eb23e,0x34a5bb64,0xbbf63872,0xb8723c00,0x3bd9b61f,0xb23eb9a8,0xbaa73b64,0xb78b3c00,0x3bf6b872,0xb913b61f,0xb4a53bd9,
0xb61f3c00,0x3b64b9a8,0xbb640000,0x361f39a8,0xb4a53c00,0x3a2fbaa7,0xbbf6361f,0x3b0e323e,0xb23e3c00,0x3872bb64,0xbaa739a8,0x3bd9b61f,0xae463c00,0x34a5bbd9,0xb78b3b64,0x3913baa7,
0x3c00,0xbc00,0x3c00,0xbc00,0x2e463c00,0xb4a5bbd9,0x378b3b64,0xb913baa7,0x323e3c00,0xb872bb64,0x3aa739a8,0xbbd9b61f,0x34a53c00,0xba2fbaa7,0x3bf6361f,0xbb0e323e,
0x361f3c00,0xbb64b9a8,0x3b640000,0xb61f39a8,0x378b3c00,0xbbf6b872,0x3913b61f,0x34a53bd9,0x38723c00,0xbbd9b61f,0x323eb9a8,0x3aa73b64,0x39133c00,0xbb0eb23e,0xb4a5bb64,0x3bf63872,
0x39a83c00,0xb9a80000,0xb9a8bc00,0x39a80000,0x3a2f3c00,0xb78b323e,0xbba8bb64,0x2e46b872,0x3aa73c00,0xb23e361f,0xbbd9b9a8,0xb872bb64,0x3b0e3c00,0x2e463872,0xba2fb61f,0xbba8bbd9,
0x3b643c00,0x361f39a8,0xb61f0000,0xbb64b9a8,0x3ba83c00,0x39133aa7,0x2e46361f,0xb78bb23e,0x3bd93c00,0x3aa73b64,0x387239a8,0x323e361f,0x3bf63c00,0x3ba83bd9,0x3b0e3b64,0x3a2f3aa7,
0,0,0,0,0x2e460000,0x34a5323e,0x378b361f,0x39133872,0x323e0000,0x3872361f,0x3aa739a8,0x3bd93b64,0x34a50000,0x3a2f3872,0x3bf63b64,0x3b0e3bd9,
0x361f0000,0x3b6439a8,0x3b643c00,0x361f39a8,0x378b0000,0x3bf63aa7,0x39133b64,0xb4a5323e,0x38720000,0x3bd93b64,0x323e39a8,0xbaa7b61f,0x39130000,0x3b0e3bd9,0xb4a5361f,0xbbf6baa7,
0x39a80000,0x39a83c00,0xb9a80000,0xb9a8bc00,0x3a2f0000,0x378b3bd9,0xbba8b61f,0xae46baa7,0x3aa70000,0x323e3b64,0xbbd9b9a8,0x3872b61f,0x3b0e0000,0xae463aa7,0xba2fbb64,0x3ba8323e,
0x3b640000,0xb61f39a8,0xb61fbc00,0x3b6439a8,0x3ba80000,0xb9133872,0x2e46bb64,0x378b3bd9,0x3bd90000,0xbaa7361f,0x3872b9a8,0xb23e3b64,0x3bf60000,0xbba8323e,0x3b0eb61f,0xba2f3872,
0x3c000000,0xbc000000,0x3c000000,0xbc000000,0x3bf60000,0xbba8b23e,0x3b0e361f,0xba2fb872,0x3bd90000,0xbaa7b61f,0x387239a8,0xb23ebb64,0x3ba80000,0xb913b872,0x2e463b64,0x378bbbd9,
0x3b640000,0xb61fb9a8,0xb61f3c00,0x3b64b9a8,0x3b0e0000,0xae46baa7,0xba2f3b64,0x3ba8b23e,0x3aa70000,0x323ebb64,0xbbd939a8,0x3872361f,0x3a2f0000,0x378bbbd9,0xbba8361f,0xae463aa7,
0x39a80000,0x39a8bc00,0xb9a80000,0xb9a83c00,0x39130000,0x3b0ebbd9,0xb4a5b61f,0xbbf63aa7,0x38720000,0x3bd9bb64,0x323eb9a8,0xbaa7361f,0x378b0000,0x3bf6baa7,0x3913bb64,0xb4a5b23e,
0x361f0000,0x3b64b9a8,0x3b64bc00,0x361fb9a8,0x34a50000,0x3a2fb872,0x3bf6bb64,0x3b0ebbd9,0x323e0000,0x3872b61f,0x3aa7b9a8,0x3bd9bb64,0x2e460000,0x34a5b23e,0x378bb61f,0x3913b872,
0,0,0,0,0xae460000,0xb4a5323e,0xb78b361f,0xb9133872,0xb23e0000,0xb872361f,0xbaa739a8,0xbbd93b64,0xb4a50000,0xba2f3872,0xbbf63b64,0xbb0e3bd9,
0xb61f0000,0xbb6439a8,0xbb643c00,0xb61f39a8,0xb78b0000,0xbbf63aa7,0xb9133b64,0x34a5323e,0xb8720000,0xbbd93b64,0xb23e39a8,0x3aa7b61f,0xb9130000,0xbb0e3bd9,0x34a5361f,0x3bf6baa7,
0xb9a80000,0xb9a83c00,0x39a80000,0x39a8bc00,0xba2f0000,0xb78b3bd9,0x3ba8b61f,0x2e46baa7,0xbaa70000,0xb23e3b64,0x3bd9b9a8,0xb872b61f,0xbb0e0000,0x2e463aa7,0x3a2fbb64,0xbba8323e,
0xbb640000,0x361f39a8,0x361fbc00,0xbb6439a8,0xbba80000,0x39133872,0xae46bb64,0xb78b3bd9,0xbbd90000,0x3aa7361f,0xb872b9a8,0x323e3b64,0xbbf60000,0x3ba8323e,0xbb0eb61f,0x3a2f3872,
0xbc000000,0x3c000000,0xbc000000,0x3c000000,0xbbf60000,0x3ba8b23e,0xbb0e361f,0x3a2fb872,0xbbd90000,0x3aa7b61f,0xb87239a8,0x323ebb64,0xbba80000,0x3913b872,0xae463b64,0xb78bbbd9,
0xbb640000,0x361fb9a8,0x361f3c00,0xbb64b9a8,0xbb0e0000,0x2e46baa7,0x3a2f3b64,0xbba8b23e,0xbaa70000,0xb23ebb64,0x3bd939a8,0xb872361f,0xba2f0000,0xb78bbbd9,0x3ba8361f,0x2e463aa7,
0xb9a80000,0xb9a8bc00,0x39a80000,0x39a83c00,0xb9130000,0xbb0ebbd9,0x34a5b61f,0x3bf63aa7,0xb8720000,0xbbd9bb64,0xb23eb9a8,0x3aa7361f,0xb78b0000,0xbbf6baa7,0xb913bb64,0x34a5b23e,
0xb61f0000,0xbb64b9a8,0xbb64bc00,0xb61fb9a8,0xb4a50000,0xba2fb872,0xbbf6bb64,0xbb0ebbd9,0xb23e0000,0xb872b61f,0xbaa7b9a8,0xbbd9bb64,0xae460000,0xb4a5b23e,0xb78bb61f,0xb913b872,
0x3c003c00,0x3c003c00,0x3c003c00,0x3c003c00,0x391339a8,0x378b3872,0x34a5361f,0x2e46323e,0xb23e0000,0xb872b61f,0xbaa7b9a8,0xbbd9bb64,0xbb0eb9a8,0xbbf6bbd9,0xba2fbb64,0xb4a5b872,
0xbb64bc00,0xb61fb9a8,0x361f0000,0x3b6439a8,0xb4a5b9a8,0x3913323e,0x3bf63b64,0x378b3aa7,0x38720000,0x3bd93b64,0x323e39a8,0xbaa7b61f,0x3bf639a8,0x34a53aa7,0xbb0eb61f,0xb913bbd9,
0x39a83c00,0xb9a80000,0xb9a8bc00,0x39a80000,0xae4639a8,0xbba8baa7,0x378bb61f,0x3a2f3bd9,0xbaa70000,0xb23ebb64,0x3bd939a8,0xb872361f,0xbba8b9a8,0x3a2fb23e,0x2e463b64,0xbb0ebaa7,
0xb61fbc00,0x3b6439a8,0xbb640000,0x361fb9a8,0x378bb9a8,0x2e463bd9,0xb913bb64,0x3ba83872,0x3bd90000,0xbaa7361f,0x3872b9a8,0xb23e3b64,0x3a2f39a8,0xbb0eb872,0x3ba8361f,0xbbf6b23e,
0x3c00,0xbc00,0x3c00,0xbc00,0xba2f39a8,0x3b0eb872,0xbba8361f,0x3bf6b23e,0xbbd90000,0x3aa7361f,0xb872b9a8,0x323e3b64,0xb78bb9a8,0xae463bd9,0x3913bb64,0xbba83872,
0x361fbc00,0xbb6439a8,0x3b640000,0xb61fb9a8,0x3ba8b9a8,0xba2fb23e,0xae463b64,0x3b0ebaa7,0x3aa70000,0x323ebb64,0xbbd939a8,0x3872361f,0x2e4639a8,0x3ba8baa7,0xb78bb61f,0xba2f3bd9,
0xb9a83c00,0x39a80000,0x39a8bc00,0xb9a80000,0xbbf639a8,0xb4a53aa7,0x3b0eb61f,0x3913bbd9,0xb8720000,0xbbd93b64,0xb23e39a8,0x3aa7b61f,0x34a5b9a8,0xb913323e,0xbbf63b64,0xb78b3aa7,
0x3b64bc00,0x361fb9a8,0xb61f0000,0xbb6439a8,0x3b0eb9a8,0x3bf6bbd9,0x3a2fbb64,0x34a5b872,0x323e0000,0x3872b61f,0x3aa7b9a8,0x3bd9bb64,0xb91339a8,0xb78b3872,0xb4a5361f,0xae46323e,
0xbc003c00,0xbc003c00,0xbc003c00,0xbc003c00,0xb91339a8,0xb78b3872,0xb4a5361f,0xae46323e,0x323e0000,0x3872b61f,0x3aa7b9a8,0x3bd9bb64,0x3b0eb9a8,0x3bf6bbd9,0x3a2fbb64,0x34a5b872,
0x3b64bc00,0x361fb9a8,0xb61f0000,0xbb6439a8,0x34a5b9a8,0xb913323e,0xbbf63b64,0xb78b3aa7,0xb8720000,0xbbd93b64,0xb23e39a8,0x3aa7b61f,0xbbf639a8,0xb4a53aa7,0x3b0eb61f,0x3913bbd9,
0xb9a83c00,0x39a80000,0x39a8bc00,0xb9a80000,0x2e4639a8,0x3ba8baa7,0xb78bb61f,0xba2f3bd9,0x3aa70000,0x323ebb64,0xbbd939a8,0x3872361f,0x3ba8b9a8,0xba2fb23e,0xae463b64,0x3b0ebaa7,
0x361fbc00,0xbb6439a8,0x3b640000,0xb61fb9a8,0xb78bb9a8,0xae463bd9,0x3913bb64,0xbba83872,0xbbd90000,0x3aa7361f,0xb872b9a8,0x323e3b64,0xba2f39a8,0x3b0eb872,0xbba8361f,0x3bf6b23e,
0x3c00,0xbc00,0x3c00,0xbc00,0x3a2f39a8,0xbb0eb872,0x3ba8361f,0xbbf6b23e,0x3bd90000,0xbaa7361f,0x3872b9a8,0xb23e3b64,0x378bb9a8,0x2e463bd9,0xb913bb64,0x3ba83872,
0xb61fbc00,0x3b6439a8,0xbb640000,0x361fb9a8,0xbba8b9a8,0x3a2fb23e,0x2e463b64,0xbb0ebaa7,0xbaa70000,0xb23ebb64,0x3bd939a8,0xb872361f,0xae4639a8,0xbba8baa7,0x378bb61f,0x3a2f3bd9,
0x39a83c00,0xb9a80000,0xb9a8bc00,0x39a80000,0x3bf639a8,0x34a53aa7,0xbb0eb61f,0xb913bbd9,0x38720000,0x3bd93b64,0x323e39a8,0xbaa7b61f,0xb4a5b9a8,0x3913323e,0x3bf63b64,0x378b3aa7,
0xbb64bc00,0xb61fb9a8,0x361f0000,0x3b6439a8,0xbb0eb9a8,0xbbf6bbd9,0xba2fbb64,0xb4a5b872,0xb23e0000,0xb872b61f,0xbaa7b9a8,0xbbd9bb64,0x391339a8,0x378b3872,0x34a5361f,0x2e46323e,
0,0,0,0,0x3a2f39a8,0x3b0e3aa7,0x3ba83b64,0x3bf63bd9,0x3bd93c00,0x3aa73b64,0x387239a8,0x323e361f,0x378b39a8,0xae46323e,0xb913b61f,0xbba8baa7,
0xb61f0000,0xbb64b9a8,0xbb64bc00,0xb61fb9a8,0xbba8b9a8,0xba2fbbd9,0x2e46b61f,0x3b0e3872,0xbaa7bc00,0x323eb61f,0x3bd939a8,0x38723b64,0xae46b9a8,0x3ba83872,0x378b3b64,0xba2fb23e,
0x39a80000,0x39a83c00,0xb9a80000,0xb9a8bc00,0x3bf639a8,0xb4a53872,0xbb0ebb64,0x3913b23e,0x38723c00,0xbbd9b61f,0x323eb9a8,0x3aa73b64,0xb4a539a8,0xb913bbd9,0x3bf6361f,0xb78b3872,
0xbb640000,0x361fb9a8,0x361f3c00,0xbb64b9a8,0xbb0eb9a8,0x3bf6323e,0xba2f361f,0x34a5baa7,0xb23ebc00,0x38723b64,0xbaa7b9a8,0x3bd9361f,0x3913b9a8,0xb78b3aa7,0x34a5bb64,0xae463bd9,
0x3c000000,0xbc000000,0x3c000000,0xbc000000,0x391339a8,0xb78bbaa7,0x34a53b64,0xae46bbd9,0xb23e3c00,0x3872bb64,0xbaa739a8,0x3bd9b61f,0xbb0e39a8,0x3bf6b23e,0xba2fb61f,0x34a53aa7,
0xbb640000,0x361f39a8,0x361fbc00,0xbb6439a8,0xb4a5b9a8,0xb9133bd9,0x3bf6b61f,0xb78bb872,0x3872bc00,0xbbd9361f,0x323e39a8,0x3aa7bb64,0x3bf6b9a8,0xb4a5b872,0xbb0e3b64,0x3913323e,
0x39a80000,0x39a8bc00,0xb9a80000,0xb9a83c00,0xae4639a8,0x3ba8b872,0x378bbb64,0xba2f323e,0xbaa73c00,0x323e361f,0x3bd9b9a8,0x3872bb64,0xbba839a8,0xba2f3bd9,0x2e46361f,0x3b0eb872,
0xb61f0000,0xbb6439a8,0xbb643c00,0xb61f39a8,0x378bb9a8,0xae46b23e,0xb913361f,0xbba83aa7,0x3bd9bc00,0x3aa7bb64,0x3872b9a8,0x323eb61f,0x3a2fb9a8,0x3b0ebaa7,0x3ba8bb64,0x3bf6bbd9,
0,0,0,0,0xba2f39a8,0xbb0e3aa7,0xbba83b64,0xbbf63bd9,0xbbd93c00,0xbaa73b64,0xb87239a8,0xb23e361f,0xb78b39a8,0x2e46323e,0x3913b61f,0x3ba8baa7,
0x361f0000,0x3b64b9a8,0x3b64bc00,0x361fb9a8,0x3ba8b9a8,0x3a2fbbd9,0xae46b61f,0xbb0e3872,0x3aa7bc00,0xb23eb61f,0xbbd939a8,0xb8723b64,0x2e46b9a8,0xbba83872,0xb78b3b64,0x3a2fb23e,
0xb9a80000,0xb9a83c00,0x39a80000,0x39a8bc00,0xbbf639a8,0x34a53872,0x3b0ebb64,0xb913b23e,0xb8723c00,0x3bd9b61f,0xb23eb9a8,0xbaa73b64,0x34a539a8,0x3913bbd9,0xbbf6361f,0x378b3872,
0x3b640000,0xb61fb9a8,0xb61f3c00,0x3b64b9a8,0x3b0eb9a8,0xbbf6323e,0x3a2f361f,0xb4a5baa7,0x323ebc00,0xb8723b64,0x3aa7b9a8,0xbbd9361f,0xb913b9a8,0x378b3aa7,0xb4a5bb64,0x2e463bd9,
0xbc000000,0x3c000000,0xbc000000,0x3c000000,0xb91339a8,0x378bbaa7,0xb4a53b64,0x2e46bbd9,0x323e3c00,0xb872bb64,0x3aa739a8,0xbbd9b61f,0x3b0e39a8,0xbbf6b23e,0x3a2fb61f,0xb4a53aa7,
0x3b640000,0xb61f39a8,0xb61fbc00,0x3b6439a8,0x34a5b9a8,0x39133bd9,0xbbf6b61f,0x378bb872,0xb872bc00,0x3bd9361f,0xb23e39a8,0xbaa7bb64,0xbbf6b9a8,0x34a5b872,0x3b0e3b64,0xb913323e,
0xb9a80000,0xb9a8bc00,0x39a80000,0x39a83c00,0x2e4639a8,0xbba8b872,0xb78bbb64,0x3a2f323e,0x3aa73c00,0xb23e361f,0xbbd9b9a8,0xb872bb64,0x3ba839a8,0x3a2f3bd9,0xae46361f,0xbb0eb872,
0x361f0000,0x3b6439a8,0x3b643c00,0x361f39a8,0xb78bb9a8,0x2e46b23e,0x3913361f,0x3ba83aa7,0xbbd9bc00,0xbaa7bb64,0xb872b9a8,0xb23eb61f,0xba2fb9a8,0xbb0ebaa7,0xbba8bb64,0xbbf6bbd9,
0x3c003c00,0x3c003c00,0x3c003c00,0x3c003c00,0xae460000,0xb4a5b23e,0xb78bb61f,0xb913b872,0xbbd9bc00,0xbaa7bb64,0xb872b9a8,0xb23eb61f,0x34a50000,0x3a2f3872,0x3bf63b64,0x3b0e3bd9,
0x3b643c00,0x361f39a8,0xb61f0000,0xbb64b9a8,0xb78b0000,0xbbf6baa7,0xb913bb64,0x34a5b23e,0xbaa7bc00,0x323eb61f,0x3bd939a8,0x38723b64,0x39130000,0x3b0e3bd9,0xb4a5361f,0xbbf6baa7,
0x39a83c00,0xb9a80000,0xb9a8bc00,0x39a80000,0xba2f0000,0xb78bbbd9,0x3ba8361f,0x2e463aa7,0xb872bc00,0x3bd9361f,0xb23e39a8,0xbaa7bb64,0x3b0e0000,0xae463aa7,0xba2fbb64,0x3ba8323e,
0x361f3c00,0xbb64b9a8,0x3b640000,0xb61f39a8,0xbba80000,0x3913b872,0xae463b64,0xb78bbbd9,0xb23ebc00,0x38723b64,0xbaa7b9a8,0x3bd9361f,0x3bf60000,0xbba8323e,0x3b0eb61f,0xba2f3872,
0x3c00,0xbc00,0x3c00,0xbc00,0xbbf60000,0x3ba8323e,0xbb0eb61f,0x3a2f3872,0x323ebc00,0xb8723b64,0x3aa7b9a8,0xbbd9361f,0x3ba80000,0xb913b872,0x2e463b64,0x378bbbd9,
0xb61f3c00,0x3b64b9a8,0xbb640000,0x361f39a8,0xbb0e0000,0x2e463aa7,0x3a2fbb64,0xbba8323e,0x3872bc00,0xbbd9361f,0x323e39a8,0x3aa7bb64,0x3a2f0000,0x378bbbd9,0xbba8361f,0xae463aa7,
0xb9a83c00,0x39a80000,0x39a8bc00,0xb9a80000,0xb9130000,0xbb0e3bd9,0x34a5361f,0x3bf6baa7,0x3aa7bc00,0xb23eb61f,0xbbd939a8,0xb8723b64,0x378b0000,0x3bf6baa7,0x3913bb64,0xb4a5b23e,
0xbb643c00,0xb61f39a8,0x361f0000,0x3b64b9a8,0xb4a50000,0xba2f3872,0xbbf63b64,0xbb0e3bd9,0x3bd9bc00,0x3aa7bb64,0x3872b9a8,0x323eb61f,0x2e460000,0x34a5b23e,0x378bb61f,0x3913b872,
0xbc003c00,0xbc003c00,0xbc003c00,0xbc003c00,0x2e460000,0x34a5b23e,0x378bb61f,0x3913b872,0x3bd9bc00,0x3aa7bb64,0x3872b9a8,0x323eb61f,0xb4a50000,0xba2f3872,0xbbf63b64,0xbb0e3bd9,
0xbb643c00,0xb61f39a8,0x361f0000,0x3b64b9a8,0x378b0000,0x3bf6baa7,0x3913bb64,0xb4a5b23e,0x3aa7bc00,0xb23eb61f,0xbbd939a8,0xb8723b64,0xb9130000,0xbb0e3bd9,0x34a5361f,0x3bf6baa7,
0xb9a83c00,0x39a80000,0x39a8bc00,0xb9a80000,0x3a2f0000,0x378bbbd9,0xbba8361f,0xae463aa7,0x3872bc00,0xbbd9361f,0x323e39a8,0x3aa7bb64,0xbb0e0000,0x2e463aa7,0x3a2fbb64,0xbba8323e,
0xb61f3c00,0x3b64b9a8,0xbb640000,0x361f39a8,0x3ba80000,0xb913b872,0x2e463b64,0x378bbbd9,0x323ebc00,0xb8723b64,0x3aa7b9a8,0xbbd9361f,0xbbf60000,0x3ba8323e,0xbb0eb61f,0x3a2f3872,
0x3c00,0xbc00,0x3c00,0xbc00,0x3bf60000,0xbba8323e,0x3b0eb61f,0xba2f3872,0xb23ebc00,0x38723b64,0xbaa7b9a8,0x3bd9361f,0xbba80000,0x3913b872,0xae463b64,0xb78bbbd9,
0x361f3c00,0xbb64b9a8,0x3b640000,0xb61f39a8,0x3b0e0000,0xae463aa7,0xba2fbb64,0x3ba8323e,0xb872bc00,0x3bd9361f,0xb23e39a8,0xbaa7bb64,0xba2f0000,0xb78bbbd9,0x3ba8361f,0x2e463aa7,
0x39a83c00,0xb9a80000,0xb9a8bc00,0x39a80000,0x39130000,0x3b0e3bd9,0xb4a5361f,0xbbf6baa7,0xbaa7bc00,0x323eb61f,0x3bd939a8,0x38723b64,0xb78b0000,0xbbf6baa7,0xb913bb64,0x34a5b23e,
0x3b643c00,0x361f39a8,0xb61f0000,0xbb64b9a8,0x34a50000,0x3a2f3872,0x3bf63b64,0x3b0e3bd9,0xbbd9bc00,0xbaa7bb64,0xb872b9a8,0xb23eb61f,0xae460000,0xb4a5b23e,0xb78bb61f,0xb913b872,
0,0,0,0,0x3bf63c00,0x3ba83bd9,0x3b0e3b64,0x3a2f3aa7,0xb23e0000,0xb872b61f,0xbaa7b9a8,0xbbd9bb64,0xbba8bc00,0xb913baa7,0xae46b61f,0x378b323e,
0x361f0000,0x3b6439a8,0x3b643c00,0x361f39a8,0x3b0e3c00,0x2e463872,0xba2fb61f,0xbba8bbd9,0xb8720000,0xbbd9bb64,0xb23eb9a8,0x3aa7361f,0xba2fbc00,0x378bb23e,0x3ba83b64,0xae463872,
0x39a80000,0x39a83c00,0xb9a80000,0xb9a8bc00,0x39133c00,0xbb0eb23e,0xb4a5bb64,0x3bf63872,0xbaa70000,0xb23ebb64,0x3bd939a8,0xb872361f,0xb78bbc00,0x3bf63872,0xb913361f,0xb4a5bbd9,
0x3b640000,0xb61f39a8,0xb61fbc00,0x3b6439a8,0x34a53c00,0xba2fbaa7,0x3bf6361f,0xbb0e323e,0xbbd90000,0x3aa7b61f,0xb87239a8,0x323ebb64,0xae46bc00,0x34a53bd9,0xb78bbb64,0x39133aa7,
0x3c000000,0xbc000000,0x3c000000,0xbc000000,0xae463c00,0x34a5bbd9,0xb78b3b64,0x3913baa7,0xbbd90000,0x3aa7361f,0xb872b9a8,0x323e3b64,0x34a5bc00,0xba2f3aa7,0x3bf6b61f,0xbb0eb23e,
0x3b640000,0xb61fb9a8,0xb61f3c00,0x3b64b9a8,0xb78b3c00,0x3bf6b872,0xb913b61f,0xb4a53bd9,0xbaa70000,0xb23e3b64,0x3bd9b9a8,0xb872b61f,0x3913bc00,0xbb0e323e,0xb4a53b64,0x3bf6b872,
0x39a80000,0x39a8bc00,0xb9a80000,0xb9a83c00,0xba2f3c00,0x378b323e,0x3ba8bb64,0xae46b872,0xb8720000,0xbbd93b64,0xb23e39a8,0x3aa7b61f,0x3b0ebc00,0x2e46b872,0xba2f361f,0xbba83bd9,
0x361f0000,0x3b64b9a8,0x3b64bc00,0x361fb9a8,0xbba83c00,0xb9133aa7,0xae46361f,0x378bb23e,0xb23e0000,0xb872361f,0xbaa739a8,0xbbd93b64,0x3bf6bc00,0x3ba8bbd9,0x3b0ebb64,0x3a2fbaa7,
0,0,0,0,0xbbf63c00,0xbba83bd9,0xbb0e3b64,0xba2f3aa7,0x323e0000,0x3872b61f,0x3aa7b9a8,0x3bd9bb64,0x3ba8bc00,0x3913baa7,0x2e46b61f,0xb78b323e,
0xb61f0000,0xbb6439a8,0xbb643c00,0xb61f39a8,0xbb0e3c00,0xae463872,0x3a2fb61f,0x3ba8bbd9,0x38720000,0x3bd9bb64,0x323eb9a8,0xbaa7361f,0x3a2fbc00,0xb78bb23e,0xbba83b64,0x2e463872,
0xb9a80000,0xb9a83c00,0x39a80000,0x39a8bc00,0xb9133c00,0x3b0eb23e,0x34a5bb64,0xbbf63872,0x3aa70000,0x323ebb64,0xbbd939a8,0x3872361f,0x378bbc00,0xbbf63872,0x3913361f,0x34a5bbd9,
0xbb640000,0x361f39a8,0x361fbc00,0xbb6439a8,0xb4a53c00,0x3a2fbaa7,0xbbf6361f,0x3b0e323e,0x3bd90000,0xbaa7b61f,0x387239a8,0xb23ebb64,0x2e46bc00,0xb4a53bd9,0x378bbb64,0xb9133aa7,
0xbc000000,0x3c000000,0xbc000000,0x3c000000,0x2e463c00,0xb4a5bbd9,0x378b3b64,0xb913baa7,0x3bd90000,0xbaa7361f,0x3872b9a8,0xb23e3b64,0xb4a5bc00,0x3a2f3aa7,0xbbf6b61f,0x3b0eb23e,
0xbb640000,0x361fb9a8,0x361f3c00,0xbb64b9a8,0x378b3c00,0xbbf6b872,0x3913b61f,0x34a53bd9,0x3aa70000,0x323e3b64,0xbbd9b9a8,0x3872b61f,0xb913bc00,0x3b0e323e,0x34a53b64,0xbbf6b872,
0xb9a80000,0xb9a8bc00,0x39a80000,0x39a83c00,0x3a2f3c00,0xb78b323e,0xbba8bb64,0x2e46b872,0x38720000,0x3bd93b64,0x323e39a8,0xbaa7b61f,0xbb0ebc00,0xae46b872,0x3a2f361f,0x3ba83bd9,
0xb61f0000,0xbb64b9a8,0xbb64bc00,0xb61fb9a8,0x3ba83c00,0x39133aa7,0x2e46361f,0xb78bb23e,0x323e0000,0x3872361f,0x3aa739a8,0x3bd93b64,0xbbf6bc00,0xbba8bbd9,0xbb0ebb64,0xba2fbaa7,
0x3c003c00,0x3c003c00,0x3c003c00,0x3c003c00,0xba2fb9a8,0xbb0ebaa7,0xbba8bb64,0xbbf6bbd9,0x323e0000,0x3872361f,0x3aa739a8,0x3bd93b64,0x378b39a8,0xae46323e,0xb913b61f,0xbba8baa7,
0xbb64bc00,0xb61fb9a8,0x361f0000,0x3b6439a8,0x3ba839a8,0x3a2f3bd9,0xae46361f,0xbb0eb872,0xb8720000,0xbbd9bb64,0xb23eb9a8,0x3aa7361f,0xae46b9a8,0x3ba83872,0x378b3b64,0xba2fb23e,
0x39a83c00,0xb9a80000,0xb9a8bc00,0x39a80000,0xbbf6b9a8,0x34a5b872,0x3b0e3b64,0xb913323e,0x3aa70000,0x323e3b64,0xbbd9b9a8,0x3872b61f,0xb4a539a8,0xb913bbd9,0x3bf6361f,0xb78b3872,
0xb61fbc00,0x3b6439a8,0xbb640000,0x361fb9a8,0x3b0e39a8,0xbbf6b23e,0x3a2fb61f,0xb4a53aa7,0xbbd90000,0x3aa7b61f,0xb87239a8,0x323ebb64,0x3913b9a8,0xb78b3aa7,0x34a5bb64,0xae463bd9,
0x3c00,0xbc00,0x3c00,0xbc00,0xb913b9a8,0x378b3aa7,0xb4a5bb64,0x2e463bd9,0x3bd90000,0xbaa7b61f,0x387239a8,0xb23ebb64,0xbb0e39a8,0x3bf6b23e,0xba2fb61f,0x34a53aa7,
0x361fbc00,0xbb6439a8,0x3b640000,0xb61fb9a8,0x34a539a8,0x3913bbd9,0xbbf6361f,0x378b3872,0xbaa70000,0xb23e3b64,0x3bd9b9a8,0xb872b61f,0x3bf6b9a8,0xb4a5b872,0xbb0e3b64,0x3913323e,
0xb9a83c00,0x39a80000,0x39a8bc00,0xb9a80000,0x2e46b9a8,0xbba83872,0xb78b3b64,0x3a2fb23e,0x38720000,0x3bd9bb64,0x323eb9a8,0xbaa7361f,0xbba839a8,0xba2f3bd9,0x2e46361f,0x3b0eb872,
0x3b64bc00,0x361fb9a8,0xb61f0000,0xbb6439a8,0xb78b39a8,0x2e46323e,0x3913b61f,0x3ba8baa7,0xb23e0000,0xb872361f,0xbaa739a8,0xbbd93b64,0x3a2fb9a8,0x3b0ebaa7,0x3ba8bb64,0x3bf6bbd9,
0xbc003c00,0xbc003c00,0xbc003c00,0xbc003c00,0x3a2fb9a8,0x3b0ebaa7,0x3ba8bb64,0x3bf6bbd9,0xb23e0000,0xb872361f,0xbaa739a8,0xbbd93b64,0xb78b39a8,0x2e46323e,0x3913b61f,0x3ba8baa7,
0x3b64bc00,0x361fb9a8,0xb61f0000,0xbb6439a8,0xbba839a8,0xba2f3bd9,0x2e46361f,0x3b0eb872,0x38720000,0x3bd9bb64,0x323eb9a8,0xbaa7361f,0x2e46b9a8,0xbba83872,0xb78b3b64,0x3a2fb23e,
0xb9a83c00,0x39a80000,0x39a8bc00,0xb9a80000,0x3bf6b9a8,0xb4a5b872,0xbb0e3b64,0x3913323e,0xbaa70000,0xb23e3b64,0x3bd9b9a8,0xb872b61f,0x34a539a8,0x3913bbd9,0xbbf6361f,0x378b3872,
0x361fbc00,0xbb6439a8,0x3b640000,0xb61fb9a8,0xbb0e39a8,0x3bf6b23e,0xba2fb61f,0x34a53aa7,0x3bd90000,0xbaa7b61f,0x387239a8,0xb23ebb64,0xb913b9a8,0x378b3aa7,0xb4a5bb64,0x2e463bd9,
0x3c00,0xbc00,0x3c00,0xbc00,0x3913b9a8,0xb78b3aa7,0x34a5bb64,0xae463bd9,0xbbd90000,0x3aa7b61f,0xb87239a8,0x323ebb64,0x3b0e39a8,0xbbf6b23e,0x3a2fb61f,0xb4a53aa7,
0xb61fbc00,0x3b6439a8,0xbb640000,0x361fb9a8,0xb4a539a8,0xb913bbd9,0x3bf6361f,0xb78b3872,0x3aa70000,0x323e3b64,0xbbd9b9a8,0x3872b61f,0xbbf6b9a8,0x34a5b872,0x3b0e3b64,0xb913323e,
0x39a83c00,0xb9a80000,0xb9a8bc00,0x39a80000,0xae46b9a8,0x3ba83872,0x378b3b64,0xba2fb23e,0xb8720000,0xbbd9bb64,0xb23eb9a8,0x3aa7361f,0x3ba839a8,0x3a2f3bd9,0xae46361f,0xbb0eb872,
0xbb64bc00,0xb61fb9a8,0x361f0000,0x3b6439a8,0x378b39a8,0xae46323e,0xb913b61f,0xbba8baa7,0x323e0000,0x3872361f,0x3aa739a8,0x3bd93b64,0xba2fb9a8,0xbb0ebaa7,0xbba8bb64,0xbbf6bbd9,
0,0,0,0,0x391339a8,0x378b3872,0x34a5361f,0x2e46323e,0xbbd9bc00,0xbaa7bb64,0xb872b9a8,0xb23eb61f,0x3b0e39a8,0x3bf63bd9,0x3a2f3b64,0x34a53872,
0xb61f0000,0xbb64b9a8,0xbb64bc00,0xb61fb9a8,0xb4a5b9a8,0x3913323e,0x3bf63b64,0x378b3aa7,0x3aa73c00,0xb23e361f,0xbbd9b9a8,0xb872bb64,0xbbf6b9a8,0xb4a5baa7,0x3b0e361f,0x39133bd9,
0x39a80000,0x39a83c00,0xb9a80000,0xb9a8bc00,0xae4639a8,0xbba8baa7,0x378bb61f,0x3a2f3bd9,0xb872bc00,0x3bd9361f,0xb23e39a8,0xbaa7bb64,0x3ba839a8,0xba2f323e,0xae46bb64,0x3b0e3aa7,
0xbb640000,0x361fb9a8,0x361f3c00,0xbb64b9a8,0x378bb9a8,0x2e463bd9,0xb913bb64,0x3ba83872,0x323e3c00,0xb872bb64,0x3aa739a8,0xbbd9b61f,0xba2fb9a8,0x3b0e3872,0xbba8b61f,0x3bf6323e,
0x3c000000,0xbc000000,0x3c000000,0xbc000000,0xba2f39a8,0x3b0eb872,0xbba8361f,0x3bf6b23e,0x323ebc00,0xb8723b64,0x3aa7b9a8,0xbbd9361f,0x378b39a8,0x2e46bbd9,0xb9133b64,0x3ba8b872,
0xbb640000,0x361f39a8,0x361fbc00,0xbb6439a8,0x3ba8b9a8,0xba2fb23e,0xae463b64,0x3b0ebaa7,0xb8723c00,0x3bd9b61f,0xb23eb9a8,0xbaa73b64,0xae46b9a8,0xbba83aa7,0x378b361f,0x3a2fbbd9,
0x39a80000,0x39a8bc00,0xb9a80000,0xb9a83c00,0xbbf639a8,0xb4a53aa7,0x3b0eb61f,0x3913bbd9,0x3aa7bc00,0xb23eb61f,0xbbd939a8,0xb8723b64,0xb4a539a8,0x3913b23e,0x3bf6bb64,0x378bbaa7,
0xb61f0000,0xbb6439a8,0xbb643c00,0xb61f39a8,0x3b0eb9a8,0x3bf6bbd9,0x3a2fbb64,0x34a5b872,0xbbd93c00,0xbaa73b64,0xb87239a8,0xb23e361f,0x3913b9a8,0x378bb872,0x34a5b61f,0x2e46b23e,
0,0,0,0,0xb91339a8,0xb78b3872,0xb4a5361f,0xae46323e,0x3bd9bc00,0x3aa7bb64,0x3872b9a8,0x323eb61f,0xbb0e39a8,0xbbf63bd9,0xba2f3b64,0xb4a53872,
0x361f0000,0x3b64b9a8,0x3b64bc00,0x361fb9a8,0x34a5b9a8,0xb913323e,0xbbf63b64,0xb78b3aa7,0xbaa73c00,0x323e361f,0x3bd9b9a8,0x3872bb64,0x3bf6b9a8,0x34a5baa7,0xbb0e361f,0xb9133bd9,
0xb9a80000,0xb9a83c00,0x39a80000,0x39a8bc00,0x2e4639a8,0x3ba8baa7,0xb78bb61f,0xba2f3bd9,0x3872bc00,0xbbd9361f,0x323e39a8,0x3aa7bb64,0xbba839a8,0x3a2f323e,0x2e46bb64,0xbb0e3aa7,
0x3b640000,0xb61fb9a8,0xb61f3c00,0x3b64b9a8,0xb78bb9a8,0xae463bd9,0x3913bb64,0xbba83872,0xb23e3c00,0x3872bb64,0xbaa739a8,0x3bd9b61f,0x3a2fb9a8,0xbb0e3872,0x3ba8b61f,0xbbf6323e,
0xbc000000,0x3c000000,0xbc000000,0x3c000000,0x3a2f39a8,0xbb0eb872,0x3ba8361f,0xbbf6b23e,0xb23ebc00,0x38723b64,0xbaa7b9a8,0x3bd9361f,0xb78b39a8,0xae46bbd9,0x39133b64,0xbba8b872,
0x3b640000,0xb61f39a8,0xb61fbc00,0x3b6439a8,0xbba8b9a8,0x3a2fb23e,0x2e463b64,0xbb0ebaa7,0x38723c00,0xbbd9b61f,0x323eb9a8,0x3aa73b64,0x2e46b9a8,0x3ba83aa7,0xb78b361f,0xba2fbbd9,
0xb9a80000,0xb9a8bc00,0x39a80000,0x39a83c00,0x3bf639a8,0x34a53aa7,0xbb0eb61f,0xb913bbd9,0xbaa7bc00,0x323eb61f,0x3bd939a8,0x38723b64,0x34a539a8,0xb913b23e,0xbbf6bb64,0xb78bbaa7,
0x361f0000,0x3b6439a8,0x3b643c00,0x361f39a8,0xbb0eb9a8,0xbbf6bbd9,0xba2fbb64,0xb4a5b872,0x3bd93c00,0x3aa73b64,0x387239a8,0x323e361f,0xb913b9a8,0xb78bb872,0xb4a5b61f,0xae46b23e,
0x3c003c00,0x3c003c00,0x3c003c00,0x3c003c00,0xbbf6bc00,0xbba8bbd9,0xbb0ebb64,0xba2fbaa7,0x3bd93c00,0x3aa73b64,0x387239a8,0x323e361f,0xbba8bc00,0xb913baa7,0xae46b61f,0x378b323e,
0x3b643c00,0x361f39a8,0xb61f0000,0xbb64b9a8,0xbb0ebc00,0xae46b872,0x3a2f361f,0x3ba83bd9,0x3aa73c00,0xb23e361f,0xbbd9b9a8,0xb872bb64,0xba2fbc00,0x378bb23e,0x3ba83b64,0xae463872,
0x39a83c00,0xb9a80000,0xb9a8bc00,0x39a80000,0xb913bc00,0x3b0e323e,0x34a53b64,0xbbf6b872,0x38723c00,0xbbd9b61f,0x323eb9a8,0x3aa73b64,0xb78bbc00,0x3bf63872,0xb913361f,0xb4a5bbd9,
0x361f3c00,0xbb64b9a8,0x3b640000,0xb61f39a8,0xb4a5bc00,0x3a2f3aa7,0xbbf6b61f,0x3b0eb23e,0x323e3c00,0xb872bb64,0x3aa739a8,0xbbd9b61f,0xae46bc00,0x34a53bd9,0xb78bbb64,0x39133aa7,
0x3c00,0xbc00,0x3c00,0xbc00,0x2e46bc00,0xb4a53bd9,0x378bbb64,0xb9133aa7,0xb23e3c00,0x3872bb64,0xbaa739a8,0x3bd9b61f,0x34a5bc00,0xba2f3aa7,0x3bf6b61f,0xbb0eb23e,
0xb61f3c00,0x3b64b9a8,0xbb640000,0x361f39a8,0x378bbc00,0xbbf63872,0x3913361f,0x34a5bbd9,0xb8723c00,0x3bd9b61f,0xb23eb9a8,0xbaa73b64,0x3913bc00,0xbb0e323e,0xb4a53b64,0x3bf6b872,
0xb9a83c00,0x39a80000,0x39a8bc00,0xb9a80000,0x3a2fbc00,0xb78bb23e,0xbba83b64,0x2e463872,0xbaa73c00,0x323e361f,0x3bd9b9a8,0x3872bb64,0x3b0ebc00,0x2e46b872,0xba2f361f,0xbba83bd9,
0xbb643c00,0xb61f39a8,0x361f0000,0x3b64b9a8,0x3ba8bc00,0x3913baa7,0x2e46b61f,0xb78b323e,0xbbd93c00,0xbaa73b64,0xb87239a8,0xb23e361f,0x3bf6bc00,0x3ba8bbd9,0x3b0ebb64,0x3a2fbaa7,
0xbc003c00,0xbc003c00,0xbc003c00,0xbc003c00,0x3bf6bc00,0x3ba8bbd9,0x3b0ebb64,0x3a2fbaa7,0xbbd93c00,0xbaa73b64,0xb87239a8,0xb23e361f,0x3ba8bc00,0x3913baa7,0x2e46b61f,0xb78b323e,
0xbb643c00,0xb61f39a8,0x361f0000,0x3b64b9a8,0x3b0ebc00,0x2e46b872,0xba2f361f,0xbba83bd9,0xbaa73c00,0x323e361f,0x3bd9b9a8,0x3872bb64,0x3a2fbc00,0xb78bb23e,0xbba83b64,0x2e463872,
0xb9a83c00,0x39a80000,0x39a8bc00,0xb9a80000,0x3913bc00,0xbb0e323e,0xb4a53b64,0x3bf6b872,0xb8723c00,0x3bd9b61f,0xb23eb9a8,0xbaa73b64,0x378bbc00,0xbbf63872,0x3913361f,0x34a5bbd9,
0xb61f3c00,0x3b64b9a8,0xbb640000,0x361f39a8,0x34a5bc00,0xba2f3aa7,0x3bf6b61f,0xbb0eb23e,0xb23e3c00,0x3872bb64,0xbaa739a8,0x3bd9b61f,0x2e46bc00,0xb4a53bd9,0x378bbb64,0xb9133aa7,
0x3c00,0xbc00,0x3c00,0xbc00,0xae46bc00,0x34a53bd9,0xb78bbb64,0x39133aa7,0x323e3c00,0xb872bb64,0x3aa739a8,0xbbd9b61f,0xb4a5bc00,0x3a2f3aa7,0xbbf6b61f,0x3b0eb23e,
0x361f3c00,0xbb64b9a8,0x3b640000,0xb61f39a8,0xb78bbc00,0x3bf63872,0xb913361f,0xb4a5bbd9,0x38723c00,0xbbd9b61f,0x323eb9a8,0x3aa73b64,0xb913bc00,0x3b0e323e,0x34a53b64,0xbbf6b872,
0x39a83c00,0xb9a80000,0xb9a8bc00,0x39a80000,0xba2fbc00,0x378bb23e,0x3ba83b64,0xae463872,0x3aa73c00,0xb23e361f,0xbbd9b9a8,0xb872bb64,0xbb0ebc00,0xae46b872,0x3a2f361f,0x3ba83bd9,
0x3b643c00,0x361f39a8,0xb61f0000,0xbb64b9a8,0xbba8bc00,0xb913baa7,0xae46b61f,0x378b323e,0x3bd93c00,0x3aa73b64,0x387239a8,0x323e361f,0xbbf6bc00,0xbba8bbd9,0xbb0ebb64,0xba2fbaa7,
0,0,0,0,0xae460000,0xb4a5b23e,0xb78bb61f,0xb913b872,0x323e0000,0x3872361f,0x3aa739a8,0x3bd93b64,0xb4a50000,0xba2fb872,0xbbf6bb64,0xbb0ebbd9,
0x361f0000,0x3b6439a8,0x3b643c00,0x361f39a8,0xb78b0000,0xbbf6baa7,0xb913bb64,0x34a5b23e,0x38720000,0x3bd93b64,0x323e39a8,0xbaa7b61f,0xb9130000,0xbb0ebbd9,0x34a5b61f,0x3bf63aa7,
0x39a80000,0x39a83c00,0xb9a80000,0xb9a8bc00,0xba2f0000,0xb78bbbd9,0x3ba8361f,0x2e463aa7,0x3aa70000,0x323e3b64,0xbbd9b9a8,0x3872b61f,0xbb0e0000,0x2e46baa7,0x3a2f3b64,0xbba8b23e,
0x3b640000,0xb61f39a8,0xb61fbc00,0x3b6439a8,0xbba80000,0x3913b872,0xae463b64,0xb78bbbd9,0x3bd90000,0xbaa7361f,0x3872b9a8,0xb23e3b64,0xbbf60000,0x3ba8b23e,0xbb0e361f,0x3a2fb872,
0x3c000000,0xbc000000,0x3c000000,0xbc000000,0xbbf60000,0x3ba8323e,0xbb0eb61f,0x3a2f3872,0x3bd90000,0xbaa7b61f,0x387239a8,0xb23ebb64,0xbba80000,0x39133872,0xae46bb64,0xb78b3bd9,
0x3b640000,0xb61fb9a8,0xb61f3c00,0x3b64b9a8,0xbb0e0000,0x2e463aa7,0x3a2fbb64,0xbba8323e,0x3aa70000,0x323ebb64,0xbbd939a8,0x3872361f,0xba2f0000,0xb78b3bd9,0x3ba8b61f,0x2e46baa7,
0x39a80000,0x39a8bc00,0xb9a80000,0xb9a83c00,0xb9130000,0xbb0e3bd9,0x34a5361f,0x3bf6baa7,0x38720000,0x3bd9bb64,0x323eb9a8,0xbaa7361f,0xb78b0000,0xbbf63aa7,0xb9133b64,0x34a5323e,
0x361f0000,0x3b64b9a8,0x3b64bc00,0x361fb9a8,0xb4a50000,0xba2f3872,0xbbf63b64,0xbb0e3bd9,0x323e0000,0x3872b61f,0x3aa7b9a8,0x3bd9bb64,0xae460000,0xb4a5323e,0xb78b361f,0xb9133872,
0,0,0,0,0x2e460000,0x34a5b23e,0x378bb61f,0x3913b872,0xb23e0000,0xb872361f,0xbaa739a8,0xbbd93b64,0x34a50000,0x3a2fb872,0x3bf6bb64,0x3b0ebbd9,
0xb61f0000,0xbb6439a8,0xbb643c00,0xb61f39a8,0x378b0000,0x3bf6baa7,0x3913bb64,0xb4a5b23e,0xb8720000,0xbbd93b64,0xb23e39a8,0x3aa7b61f,0x39130000,0x3b0ebbd9,0xb4a5b61f,0xbbf63aa7,
0xb9a80000,0xb9a83c00,0x39a80000,0x39a8bc00,0x3a2f0000,0x378bbbd9,0xbba8361f,0xae463aa7,0xbaa70000,0xb23e3b64,0x3bd9b9a8,0xb872b61f,0x3b0e0000,0xae46baa7,0xba2f3b64,0x3ba8b23e,
0xbb640000,0x361f39a8,0x361fbc00,0xbb6439a8,0x3ba80000,0xb913b872,0x2e463b64,0x378bbbd9,0xbbd90000,0x3aa7361f,0xb872b9a8,0x323e3b64,0x3bf60000,0xbba8b23e,0x3b0e361f,0xba2fb872,
0xbc000000,0x3c000000,0xbc000000,0x3c000000,0x3bf60000,0xbba8323e,0x3b0eb61f,0xba2f3872,0xbbd90000,0x3aa7b61f,0xb87239a8,0x323ebb64,0x3ba80000,0xb9133872,0x2e46bb64,0x378b3bd9,
0xbb640000,0x361fb9a8,0x361f3c00,0xbb64b9a8,0x3b0e0000,0xae463aa7,0xba2fbb64,0x3ba8323e,0xbaa70000,0xb23ebb64,0x3bd939a8,0xb872361f,0x3a2f0000,0x378b3bd9,0xbba8b61f,0xae46baa7,
0xb9a80000,0xb9a8bc00,0x39a80000,0x39a83c00,0x39130000,0x3b0e3bd9,0xb4a5361f,0xbbf6baa7,0xb8720000,0xbbd9bb64,0xb23eb9a8,0x3aa7361f,0x378b0000,0x3bf63aa7,0x39133b64,0xb4a5323e,
0xb61f0000,0xbb64b9a8,0xbb64bc00,0xb61fb9a8,0x34a50000,0x3a2f3872,0x3bf63b64,0x3b0e3bd9,0xb23e0000,0xb872b61f,0xbaa7b9a8,0xbbd9bb64,0x2e460000,0x34a5323e,0x378b361f,0x39133872,
0x3c003c00,0x3c003c00,0x3c003c00,0x3c003c00,0xb913b9a8,0xb78bb872,0xb4a5b61f,0xae46b23e,0xb23e0000,0xb872b61f,0xbaa7b9a8,0xbbd9bb64,0x3b0e39a8,0x3bf63bd9,0x3a2f3b64,0x34a53872,
0xbb64bc00,0xb61fb9a8,0x361f0000,0x3b6439a8,0x34a539a8,0xb913b23e,0xbbf6bb64,0xb78bbaa7,0x38720000,0x3bd93b64,0x323e39a8,0xbaa7b61f,0xbbf6b9a8,0xb4a5baa7,0x3b0e361f,0x39133bd9,
0x39a83c00,0xb9a80000,0xb9a8bc00,0x39a80000,0x2e46b9a8,0x3ba83aa7,0xb78b361f,0xba2fbbd9,0xbaa70000,0xb23ebb64,0x3bd939a8,0xb872361f,0x3ba839a8,0xba2f323e,0xae46bb64,0x3b0e3aa7,
0xb61fbc00,0x3b6439a8,0xbb640000,0x361fb9a8,0xb78b39a8,0xae46bbd9,0x39133b64,0xbba8b872,0x3bd90000,0xbaa7361f,0x3872b9a8,0xb23e3b64,0xba2fb9a8,0x3b0e3872,0xbba8b61f,0x3bf6323e,
0x3c00,0xbc00,0x3c00,0xbc00,0x3a2fb9a8,0xbb0e3872,0x3ba8b61f,0xbbf6323e,0xbbd90000,0x3aa7361f,0xb872b9a8,0x323e3b64,0x378b39a8,0x2e46bbd9,0xb9133b64,0x3ba8b872,
0x361fbc00,0xbb6439a8,0x3b640000,0xb61fb9a8,0xbba839a8,0x3a2f323e,0x2e46bb64,0xbb0e3aa7,0x3aa70000,0x323ebb64,0xbbd939a8,0x3872361f,0xae46b9a8,0xbba83aa7,0x378b361f,0x3a2fbbd9,
0xb9a83c00,0x39a80000,0x39a8bc00,0xb9a80000,0x3bf6b9a8,0x34a5baa7,0xbb0e361f,0xb9133bd9,0xb8720000,0xbbd93b64,0xb23e39a8,0x3aa7b61f,0xb4a539a8,0x3913b23e,0x3bf6bb64,0x378bbaa7,
0x3b64bc00,0x361fb9a8,0xb61f0000,0xbb6439a8,0xbb0e39a8,0xbbf63bd9,0xba2f3b64,0xb4a53872,0x323e0000,0x3872b61f,0x3aa7b9a8,0x3bd9bb64,0x3913b9a8,0x378bb872,0x34a5b61f,0x2e46b23e,
0xbc003c00,0xbc003c00,0xbc003c00,0xbc003c00,0x3913b9a8,0x378bb872,0x34a5b61f,0x2e46b23e,0x323e0000,0x3872b61f,0x3aa7b9a8,0x3bd9bb64,0xbb0e39a8,0xbbf63bd9,0xba2f3b64,0xb4a53872,
0x3b64bc00,0x361fb9a8,0xb61f0000,0xbb6439a8,0xb4a539a8,0x3913b23e,0x3bf6bb64,0x378bbaa7,0xb8720000,0xbbd93b64,0xb23e39a8,0x3aa7b61f,0x3bf6b9a8,0x34a5baa7,0xbb0e361f,0xb9133bd9,
0xb9a83c00,0x39a80000,0x39a8bc00,0xb9a80000,0xae46b9a8,0xbba83aa7,0x378b361f,0x3a2fbbd9,0x3aa70000,0x323ebb64,0xbbd939a8,0x3872361f,0xbba839a8,0x3a2f323e,0x2e46bb64,0xbb0e3aa7,
0x361fbc00,0xbb6439a8,0x3b640000,0xb61fb9a8,0x378b39a8,0x2e46bbd9,0xb9133b64,0x3ba8b872,0xbbd90000,0x3aa7361f,0xb872b9a8,0x323e3b64,0x3a2fb9a8,0xbb0e3872,0x3ba8b61f,0xbbf6323e,
0x3c00,0xbc00,0x3c00,0xbc00,0xba2fb9a8,0x3b0e3872,0xbba8b61f,0x3bf6323e,0x3bd90000,0xbaa7361f,0x3872b9a8,0xb23e3b64,0xb78b39a8,0xae46bbd9,0x39133b64,0xbba8b872,
0xb61fbc00,0x3b6439a8,0xbb640000,0x361fb9a8,0x3ba839a8,0xba2f323e,0xae46bb64,0x3b0e3aa7,0xbaa70000,0xb23ebb64,0x3bd939a8,0xb872361f,0x2e46b9a8,0x3ba83aa7,0xb78b361f,0xba2fbbd9,
0x39a83c00,0xb9a80000,0xb9a8bc00,0x39a80000,0xbbf6b9a8,0xb4a5baa7,0x3b0e361f,0x39133bd9,0x38720000,0x3bd93b64,0x323e39a8,0xbaa7b61f,0x34a539a8,0xb913b23e,0xbbf6bb64,0xb78bbaa7,
0xbb64bc00,0xb61fb9a8,0x361f0000,0x3b6439a8,0x3b0e39a8,0x3bf63bd9,0x3a2f3b64,0x34a53872,0xb23e0000,0xb872b61f,0xbaa7b9a8,0xbbd9bb64,0xb913b9a8,0xb78bb872,0xb4a5b61f,0xae46b23e,
0,0,0,0,0xba2fb9a8,0xbb0ebaa7,0xbba8bb64,0xbbf6bbd9,0x3bd93c00,0x3aa73b64,0x387239a8,0x323e361f,0xb78bb9a8,0x2e46b23e,0x3913361f,0x3ba83aa7,
0xb61f0000,0xbb64b9a8,0xbb64bc00,0xb61fb9a8,0x3ba839a8,0x3a2f3bd9,0xae46361f,0xbb0eb872,0xbaa7bc00,0x323eb61f,0x3bd939a8,0x38723b64,0x2e4639a8,0xbba8b872,0xb78bbb64,0x3a2f323e,
0x39a80000,0x39a83c00,0xb9a80000,0xb9a8bc00,0xbbf6b9a8,0x34a5b872,0x3b0e3b64,0xb913323e,0x38723c00,0xbbd9b61f,0x323eb9a8,0x3aa73b64,0x34a5b9a8,0x39133bd9,0xbbf6b61f,0x378bb872,
0xbb640000,0x361fb9a8,0x361f3c00,0xbb64b9a8,0x3b0e39a8,0xbbf6b23e,0x3a2fb61f,0xb4a53aa7,0xb23ebc00,0x38723b64,0xbaa7b9a8,0x3bd9361f,0xb91339a8,0x378bbaa7,0xb4a53b64,0x2e46bbd9,
0x3c000000,0xbc000000,0x3c000000,0xbc000000,0xb913b9a8,0x378b3aa7,0xb4a5bb64,0x2e463bd9,0xb23e3c00,0x3872bb64,0xbaa739a8,0x3bd9b61f,0x3b0eb9a8,0xbbf6323e,0x3a2f361f,0xb4a5baa7,
0xbb640000,0x361f39a8,0x361fbc00,0xbb6439a8,0x34a539a8,0x3913bbd9,0xbbf6361f,0x378b3872,0x3872bc00,0xbbd9361f,0x323e39a8,0x3aa7bb64,0xbbf639a8,0x34a53872,0x3b0ebb64,0xb913b23e,
0x39a80000,0x39a8bc00,0xb9a80000,0xb9a83c00,0x2e46b9a8,0xbba83872,0xb78b3b64,0x3a2fb23e,0xbaa73c00,0x323e361f,0x3bd9b9a8,0x3872bb64,0x3ba8b9a8,0x3a2fbbd9,0xae46b61f,0xbb0e3872,
0xb61f0000,0xbb6439a8,0xbb643c00,0xb61f39a8,0xb78b39a8,0x2e46323e,0x3913b61f,0x3ba8baa7,0x3bd9bc00,0x3aa7bb64,0x3872b9a8,0x323eb61f,0xba2f39a8,0xbb0e3aa7,0xbba83b64,0xbbf63bd9,
0,0,0,0,0x3a2fb9a8,0x3b0ebaa7,0x3ba8bb64,0x3bf6bbd9,0xbbd93c00,0xbaa73b64,0xb87239a8,0xb23e361f,0x378bb9a8,0xae46b23e,0xb913361f,0xbba83aa7,
0x361f0000,0x3b64b9a8,0x3b64bc00,0x361fb9a8,0xbba839a8,0xba2f3bd9,0x2e46361f,0x3b0eb872,0x3aa7bc00,0xb23eb61f,0xbbd939a8,0xb8723b64,0xae4639a8,0x3ba8b872,0x378bbb64,0xba2f323e,
0xb9a80000,0xb9a83c00,0x39a80000,0x39a8bc00,0x3bf6b9a8,0xb4a5b872,0xbb0e3b64,0x3913323e,0xb8723c00,0x3bd9b61f,0xb23eb9a8,0xbaa73b64,0xb4a5b9a8,0xb9133bd9,0x3bf6b61f,0xb78bb872,
0x3b640000,0xb61fb9a8,0xb61f3c00,0x3b64b9a8,0xbb0e39a8,0x3bf6b23e,0xba2fb61f,0x34a53aa7,0x323ebc00,0xb8723b64,0x3aa7b9a8,0xbbd9361f,0x391339a8,0xb78bbaa7,0x34a53b64,0xae46bbd9,
0xbc000000,0x3c000000,0xbc000000,0x3c000000,0x3913b9a8,0xb78b3aa7,0x34a5bb64,0xae463bd9,0x323e3c00,0xb872bb64,0x3aa739a8,0xbbd9b61f,0xbb0eb9a8,0x3bf6323e,0xba2f361f,0x34a5baa7,
0x3b640000,0xb61f39a8,0xb61fbc00,0x3b6439a8,0xb4a539a8,0xb913bbd9,0x3bf6361f,0xb78b3872,0xb872bc00,0x3bd9361f,0xb23e39a8,0xbaa7bb64,0x3bf639a8,0xb4a53872,0xbb0ebb64,0x3913b23e,
0xb9a80000,0xb9a8bc00,0x39a80000,0x39a83c00,0xae46b9a8,0x3ba83872,0x378b3b64,0xba2fb23e,0x3aa73c00,0xb23e361f,0xbbd9b9a8,0xb872bb64,0xbba8b9a8,0xba2fbbd9,0x2e46b61f,0x3b0e3872,
0x361f0000,0x3b6439a8,0x3b643c00,0x361f39a8,0x378b39a8,0xae46323e,0xb913b61f,0xbba8baa7,0xbbd9bc00,0xbaa7bb64,0xb872b9a8,0xb23eb61f,0x3a2f39a8,0x3b0e3aa7,0x3ba83b64,0x3bf63bd9,
0x3c003c00,0x3c003c00,0x3c003c00,0x3c003c00,0x2e460000,0x34a5323e,0x378b361f,0x39133872,0xbbd9bc00,0xbaa7bb64,0xb872b9a8,0xb23eb61f,0xb4a50000,0xba2fb872,0xbbf6bb64,0xbb0ebbd9,
0x3b643c00,0x361f39a8,0xb61f0000,0xbb64b9a8,0x378b0000,0x3bf63aa7,0x39133b64,0xb4a5323e,0xbaa7bc00,0x323eb61f,0x3bd939a8,0x38723b64,0xb9130000,0xbb0ebbd9,0x34a5b61f,0x3bf63aa7,
0x39a83c00,0xb9a80000,0xb9a8bc00,0x39a80000,0x3a2f0000,0x378b3bd9,0xbba8b61f,0xae46baa7,0xb872bc00,0x3bd9361f,0xb23e39a8,0xbaa7bb64,0xbb0e0000,0x2e46baa7,0x3a2f3b64,0xbba8b23e,
0x361f3c00,0xbb64b9a8,0x3b640000,0xb61f39a8,0x3ba80000,0xb9133872,0x2e46bb64,0x378b3bd9,0xb23ebc00,0x38723b64,0xbaa7b9a8,0x3bd9361f,0xbbf60000,0x3ba8b23e,0xbb0e361f,0x3a2fb872,
0x3c00,0xbc00,0x3c00,0xbc00,0x3bf60000,0xbba8b23e,0x3b0e361f,0xba2fb872,0x323ebc00,0xb8723b64,0x3aa7b9a8,0xbbd9361f,0xbba80000,0x39133872,0xae46bb64,0xb78b3bd9,
0xb61f3c00,0x3b64b9a8,0xbb640000,0x361f39a8,0x3b0e0000,0xae46baa7,0xba2f3b64,0x3ba8b23e,0x3872bc00,0xbbd9361f,0x323e39a8,0x3aa7bb64,0xba2f0000,0xb78b3bd9,0x3ba8b61f,0x2e46baa7,
0xb9a83c00,0x39a80000,0x39a8bc00,0xb9a80000,0x39130000,0x3b0ebbd9,0xb4a5b61f,0xbbf63aa7,0x3aa7bc00,0xb23eb61f,0xbbd939a8,0xb8723b64,0xb78b0000,0xbbf63aa7,0xb9133b64,0x34a5323e,
0xbb643c00,0xb61f39a8,0x361f0000,0x3b64b9a8,0x34a50000,0x3a2fb872,0x3bf6bb64,0x3b0ebbd9,0x3bd9bc00,0x3aa7bb64,0x3872b9a8,0x323eb61f,0xae460000,0xb4a5323e,0xb78b361f,0xb9133872,
0xbc003c00,0xbc003c00,0xbc003c00,0xbc003c00,0xae460000,0xb4a5323e,0xb78b361f,0xb9133872,0x3bd9bc00,0x3aa7bb64,0x3872b9a8,0x323eb61f,0x34a50000,0x3a2fb872,0x3bf6bb64,0x3b0ebbd9,
0xbb643c00,0xb61f39a8,0x361f0000,0x3b64b9a8,0xb78b0000,0xbbf63aa7,0xb9133b64,0x34a5323e,0x3aa7bc00,0xb23eb61f,0xbbd939a8,0xb8723b64,0x39130000,0x3b0ebbd9,0xb4a5b61f,0xbbf63aa7,
0xb9a83c00,0x39a80000,0x39a8bc00,0xb9a80000,0xba2f0000,0xb78b3bd9,0x3ba8b61f,0x2e46baa7,0x3872bc00,0xbbd9361f,0x323e39a8,0x3aa7bb64,0x3b0e0000,0xae46baa7,0xba2f3b64,0x3ba8b23e,
0xb61f3c00,0x3b64b9a8,0xbb640000,0x361f39a8,0xbba80000,0x39133872,0xae46bb64,0xb78b3bd9,0x323ebc00,0xb8723b64,0x3aa7b9a8,0xbbd9361f,0x3bf60000,0xbba8b23e,0x3b0e361f,0xba2fb872,
0x3c00,0xbc00,0x3c00,0xbc00,0xbbf60000,0x3ba8b23e,0xbb0e361f,0x3a2fb872,0xb23ebc00,0x38723b64,0xbaa7b9a8,0x3bd9361f,0x3ba80000,0xb9133872,0x2e46bb64,0x378b3bd9,
0x361f3c00,0xbb64b9a8,0x3b640000,0xb61f39a8,0xbb0e0000,0x2e46baa7,0x3a2f3b64,0xbba8b23e,0xb872bc00,0x3bd9361f,0xb23e39a8,0xbaa7bb64,0x3a2f0000,0x378b3bd9,0xbba8b61f,0xae46baa7,
0x39a83c00,0xb9a80000,0xb9a8bc00,0x39a80000,0xb9130000,0xbb0ebbd9,0x34a5b61f,0x3bf63aa7,0xbaa7bc00,0x323eb61f,0x3bd939a8,0x38723b64,0x378b0000,0x3bf63aa7,0x39133b64,0xb4a5323e,
0x3b643c00,0x361f39a8,0xb61f0000,0xbb64b9a8,0xb4a50000,0xba2fb872,0xbbf6bb64,0xbb0ebbd9,0xbbd9bc00,0xbaa7bb64,0xb872b9a8,0xb23eb61f,0x2e460000,0x34a5323e,0x378b361f,0x39133872,
0,0,0,0,0xbbf6bc00,0xbba8bbd9,0xbb0ebb64,0xba2fbaa7,0xb23e0000,0xb872b61f,0xbaa7b9a8,0xbbd9bb64,0x3ba83c00,0x39133aa7,0x2e46361f,0xb78bb23e,
0x361f0000,0x3b6439a8,0x3b643c00,0x361f39a8,0xbb0ebc00,0xae46b872,0x3a2f361f,0x3ba83bd9,0xb8720000,0xbbd9bb64,0xb23eb9a8,0x3aa7361f,0x3a2f3c00,0xb78b323e,0xbba8bb64,0x2e46b872,
0x39a80000,0x39a83c00,0xb9a80000,0xb9a8bc00,0xb913bc00,0x3b0e323e,0x34a53b64,0xbbf6b872,0xbaa70000,0xb23ebb64,0x3bd939a8,0xb872361f,0x378b3c00,0xbbf6b872,0x3913b61f,0x34a53bd9,
0x3b640000,0xb61f39a8,0xb61fbc00,0x3b6439a8,0xb4a5bc00,0x3a2f3aa7,0xbbf6b61f,0x3b0eb23e,0xbbd90000,0x3aa7b61f,0xb87239a8,0x323ebb64,0x2e463c00,0xb4a5bbd9,0x378b3b64,0xb913baa7,
0x3c000000,0xbc000000,0x3c000000,0xbc000000,0x2e46bc00,0xb4a53bd9,0x378bbb64,0xb9133aa7,0xbbd90000,0x3aa7361f,0xb872b9a8,0x323e3b64,0xb4a53c00,0x3a2fbaa7,0xbbf6361f,0x3b0e323e,
0x3b640000,0xb61fb9a8,0xb61f3c00,0x3b64b9a8,0x378bbc00,0xbbf63872,0x3913361f,0x34a5bbd9,0xbaa70000,0xb23e3b64,0x3bd9b9a8,0xb872b61f,0xb9133c00,0x3b0eb23e,0x34a5bb64,0xbbf63872,
0x39a80000,0x39a8bc00,0xb9a80000,0xb9a83c00,0x3a2fbc00,0xb78bb23e,0xbba83b64,0x2e463872,0xb8720000,0xbbd93b64,0xb23e39a8,0x3aa7b61f,0xbb0e3c00,0xae463872,0x3a2fb61f,0x3ba8bbd9,
0x361f0000,0x3b64b9a8,0x3b64bc00,0x361fb9a8,0x3ba8bc00,0x3913baa7,0x2e46b61f,0xb78b323e,0xb23e0000,0xb872361f,0xbaa739a8,0xbbd93b64,0xbbf63c00,0xbba83bd9,0xbb0e3b64,0xba2f3aa7,
0,0,0,0,0x3bf6bc00,0x3ba8bbd9,0x3b0ebb64,0x3a2fbaa7,0x323e0000,0x3872b61f,0x3aa7b9a8,0x3bd9bb64,0xbba83c00,0xb9133aa7,0xae46361f,0x378bb23e,
0xb61f0000,0xbb6439a8,0xbb643c00,0xb61f39a8,0x3b0ebc00,0x2e46b872,0xba2f361f,0xbba83bd9,0x38720000,0x3bd9bb64,0x323eb9a8,0xbaa7361f,0xba2f3c00,0x378b323e,0x3ba8bb64,0xae46b872,
0xb9a80000,0xb9a83c00,0x39a80000,0x39a8bc00,0x3913bc00,0xbb0e323e,0xb4a53b64,0x3bf6b872,0x3aa70000,0x323ebb64,0xbbd939a8,0x3872361f,0xb78b3c00,0x3bf6b872,0xb913b61f,0xb4a53bd9,
0xbb640000,0x361f39a8,0x361fbc00,0xbb6439a8,0x34a5bc00,0xba2f3aa7,0x3bf6b61f,0xbb0eb23e,0x3bd90000,0xbaa7b61f,0x387239a8,0xb23ebb64,0xae463c00,0x34a5bbd9,0xb78b3b64,0x3913baa7,
0xbc000000,0x3c000000,0xbc000000,0x3c000000,0xae46bc00,0x34a53bd9,0xb78bbb64,0x39133aa7,0x3bd90000,0xbaa7361f,0x3872b9a8,0xb23e3b64,0x34a53c00,0xba2fbaa7,0x3bf6361f,0xbb0e323e,
0xbb640000,0x361fb9a8,0x361f3c00,0xbb64b9a8,0xb78bbc00,0x3bf63872,0xb913361f,0xb4a5bbd9,0x3aa70000,0x323e3b64,0xbbd9b9a8,0x3872b61f,0x39133c00,0xbb0eb23e,0xb4a5bb64,0x3bf63872,
0xb9a80000,0xb9a8bc00,0x39a80000,0x39a83c00,0xba2fbc00,0x378bb23e,0x3ba83b64,0xae463872,0x38720000,0x3bd93b64,0x323e39a8,0xbaa7b61f,0x3b0e3c00,0x2e463872,0xba2fb61f,0xbba8bbd9,
0xb61f0000,0xbb64b9a8,0xbb64bc00,0xb61fb9a8,0xbba8bc00,0xb913baa7,0xae46b61f,0x378b323e,0x323e0000,0x3872361f,0x3aa739a8,0x3bd93b64,0x3bf63c00,0x3ba83bd9,0x3b0e3b64,0x3a2f3aa7,
0x3c003c00,0x3c003c00,0x3c003c00,0x3c003c00,0x3a2f39a8,0x3b0e3aa7,0x3ba83b64,0x3bf63bd9,0x323e0000,0x3872361f,0x3aa739a8,0x3bd93b64,0xb78bb9a8,0x2e46b23e,0x3913361f,0x3ba83aa7,
0xbb64bc00,0xb61fb9a8,0x361f0000,0x3b6439a8,0xbba8b9a8,0xba2fbbd9,0x2e46b61f,0x3b0e3872,0xb8720000,0xbbd9bb64,0xb23eb9a8,0x3aa7361f,0x2e4639a8,0xbba8b872,0xb78bbb64,0x3a2f323e,
0x39a83c00,0xb9a80000,0xb9a8bc00,0x39a80000,0x3bf639a8,0xb4a53872,0xbb0ebb64,0x3913b23e,0x3aa70000,0x323e3b64,0xbbd9b9a8,0x3872b61f,0x34a5b9a8,0x39133bd9,0xbbf6b61f,0x378bb872,
0xb61fbc00,0x3b6439a8,0xbb640000,0x361fb9a8,0xbb0eb9a8,0x3bf6323e,0xba2f361f,0x34a5baa7,0xbbd90000,0x3aa7b61f,0xb87239a8,0x323ebb64,0xb91339a8,0x378bbaa7,0xb4a53b64,0x2e46bbd9,
0x3c00,0xbc00,0x3c00,0xbc00,0x391339a8,0xb78bbaa7,0x34a53b64,0xae46bbd9,0x3bd90000,0xbaa7b61f,0x387239a8,0xb23ebb64,0x3b0eb9a8,0xbbf6323e,0x3a2f361f,0xb4a5baa7,
0x361fbc00,0xbb6439a8,0x3b640000,0xb61fb9a8,0xb4a5b9a8,0xb9133bd9,0x3bf6b61f,0xb78bb872,0xbaa70000,0xb23e3b64,0x3bd9b9a8,0xb872b61f,0xbbf639a8,0x34a53872,0x3b0ebb64,0xb913b23e,
0xb9a83c00,0x39a80000,0x39a8bc00,0xb9a80000,0xae4639a8,0x3ba8b872,0x378bbb64,0xba2f323e,0x38720000,0x3bd9bb64,0x323eb9a8,0xbaa7361f,0x3ba8b9a8,0x3a2fbbd9,0xae46b61f,0xbb0e3872,
0x3b64bc00,0x361fb9a8,0xb61f0000,0xbb6439a8,0x378bb9a8,0xae46b23e,0xb913361f,0xbba83aa7,0xb23e0000,0xb872361f,0xbaa739a8,0xbbd93b64,0xba2f39a8,0xbb0e3aa7,0xbba83b64,0xbbf63bd9,
0xbc003c00,0xbc003c00,0xbc003c00,0xbc003c00,0xba2f39a8,0xbb0e3aa7,0xbba83b64,0xbbf63bd9,0xb23e0000,0xb872361f,0xbaa739a8,0xbbd93b64,0x378bb9a8,0xae46b23e,0xb913361f,0xbba83aa7,
0x3b64bc00,0x361fb9a8,0xb61f0000,0xbb6439a8,0x3ba8b9a8,0x3a2fbbd9,0xae46b61f,0xbb0e3872,0x38720000,0x3bd9bb64,0x323eb9a8,0xbaa7361f,0xae4639a8,0x3ba8b872,0x378bbb64,0xba2f323e,
0xb9a83c00,0x39a80000,0x39a8bc00,0xb9a80000,0xbbf639a8,0x34a53872,0x3b0ebb64,0xb913b23e,0xbaa70000,0xb23e3b64,0x3bd9b9a8,0xb872b61f,0xb4a5b9a8,0xb9133bd9,0x3bf6b61f,0xb78bb872,
0x361fbc00,0xbb6439a8,0x3b640000,0xb61fb9a8,0x3b0eb9a8,0xbbf6323e,0x3a2f361f,0xb4a5baa7,0x3bd90000,0xbaa7b61f,0x387239a8,0xb23ebb64,0x391339a8,0xb78bbaa7,0x34a53b64,0xae46bbd9,
0x3c00,0xbc00,0x3c00,0xbc00,0xb91339a8,0x378bbaa7,0xb4a53b64,0x2e46bbd9,0xbbd90000,0x3aa7b61f,0xb87239a8,0x323ebb64,0xbb0eb9a8,0x3bf6323e,0xba2f361f,0x34a5baa7,
0xb61fbc00,0x3b6439a8,0xbb640000,0x361fb9a8,0x34a5b9a8,0x39133bd9,0xbbf6b61f,0x378bb872,0x3aa70000,0x323e3b64,0xbbd9b9a8,0x3872b61f,0x3bf639a8,0xb4a53872,0xbb0ebb64,0x3913b23e,
0x39a83c00,0xb9a80000,0xb9a8bc00,0x39a80000,0x2e4639a8,0xbba8b872,0xb78bbb64,0x3a2f323e,0xb8720000,0xbbd9bb64,0xb23eb9a8,0x3aa7361f,0xbba8b9a8,0xba2fbbd9,0x2e46b61f,0x3b0e3872,
0xbb64bc00,0xb61fb9a8,0x361f0000,0x3b6439a8,0xb78bb9a8,0x2e46b23e,0x3913361f,0x3ba83aa7,0x323e0000,0x3872361f,0x3aa739a8,0x3bd93b64,0x3a2f39a8,0x3b0e3aa7,0x3ba83b64,0x3bf63bd9,
0,0,0,0,0xb913b9a8,0xb78bb872,0xb4a5b61f,0xae46b23e,0xbbd9bc00,0xbaa7bb64,0xb872b9a8,0xb23eb61f,0xbb0eb9a8,0xbbf6bbd9,0xba2fbb64,0xb4a5b872,
0xb61f0000,0xbb64b9a8,0xbb64bc00,0xb61fb9a8,0x34a539a8,0xb913b23e,0xbbf6bb64,0xb78bbaa7,0x3aa73c00,0xb23e361f,0xbbd9b9a8,0xb872bb64,0x3bf639a8,0x34a53aa7,0xbb0eb61f,0xb913bbd9,
0x39a80000,0x39a83c00,0xb9a80000,0xb9a8bc00,0x2e46b9a8,0x3ba83aa7,0xb78b361f,0xba2fbbd9,0xb872bc00,0x3bd9361f,0xb23e39a8,0xbaa7bb64,0xbba8b9a8,0x3a2fb23e,0x2e463b64,0xbb0ebaa7,
0xbb640000,0x361fb9a8,0x361f3c00,0xbb64b9a8,0xb78b39a8,0xae46bbd9,0x39133b64,0xbba8b872,0x323e3c00,0xb872bb64,0x3aa739a8,0xbbd9b61f,0x3a2f39a8,0xbb0eb872,0x3ba8361f,0xbbf6b23e,
0x3c000000,0xbc000000,0x3c000000,0xbc000000,0x3a2fb9a8,0xbb0e3872,0x3ba8b61f,0xbbf6323e,0x323ebc00,0xb8723b64,0x3aa7b9a8,0xbbd9361f,0xb78bb9a8,0xae463bd9,0x3913bb64,0xbba83872,
0xbb640000,0x361f39a8,0x361fbc00,0xbb6439a8,0xbba839a8,0x3a2f323e,0x2e46bb64,0xbb0e3aa7,0xb8723c00,0x3bd9b61f,0xb23eb9a8,0xbaa73b64,0x2e4639a8,0x3ba8baa7,0xb78bb61f,0xba2f3bd9,
0x39a80000,0x39a8bc00,0xb9a80000,0xb9a83c00,0x3bf6b9a8,0x34a5baa7,0xbb0e361f,0xb9133bd9,0x3aa7bc00,0xb23eb61f,0xbbd939a8,0xb8723b64,0x34a5b9a8,0xb913323e,0xbbf63b64,0xb78b3aa7,
0xb61f0000,0xbb6439a8,0xbb643c00,0xb61f39a8,0xbb0e39a8,0xbbf63bd9,0xba2f3b64,0xb4a53872,0xbbd93c00,0xbaa73b64,0xb87239a8,0xb23e361f,0xb91339a8,0xb78b3872,0xb4a5361f,0xae46323e,
0,0,0,0,0x3913b9a8,0x378bb872,0x34a5b61f,0x2e46b23e,0x3bd9bc00,0x3aa7bb64,0x3872b9a8,0x323eb61f,0x3b0eb9a8,0x3bf6bbd9,0x3a2fbb64,0x34a5b872,
0x361f0000,0x3b64b9a8,0x3b64bc00,0x361fb9a8,0xb4a539a8,0x3913b23e,0x3bf6bb64,0x378bbaa7,0xbaa73c00,0x323e361f,0x3bd9b9a8,0x3872bb64,0xbbf639a8,0xb4a53aa7,0x3b0eb61f,0x3913bbd9,
0xb9a80000,0xb9a83c00,0x39a80000,0x39a8bc00,0xae46b9a8,0xbba83aa7,0x378b361f,0x3a2fbbd9,0x3872bc00,0xbbd9361f,0x323e39a8,0x3aa7bb64,0x3ba8b9a8,0xba2fb23e,0xae463b64,0x3b0ebaa7,
0x3b640000,0xb61fb9a8,0xb61f3c00,0x3b64b9a8,0x378b39a8,0x2e46bbd9,0xb9133b64,0x3ba8b872,0xb23e3c00,0x3872bb64,0xbaa739a8,0x3bd9b61f,0xba2f39a8,0x3b0eb872,0xbba8361f,0x3bf6b23e,
0xbc000000,0x3c000000,0xbc000000,0x3c000000,0xba2fb9a8,0x3b0e3872,0xbba8b61f,0x3bf6323e,0xb23ebc00,0x38723b64,0xbaa7b9a8,0x3bd9361f,0x378bb9a8,0x2e463bd9,0xb913bb64,0x3ba83872,
0x3b640000,0xb61f39a8,0xb61fbc00,0x3b6439a8,0x3ba839a8,0xba2f323e,0xae46bb64,0x3b0e3aa7,0x38723c00,0xbbd9b61f,0x323eb9a8,0x3aa73b64,0xae4639a8,0xbba8baa7,0x378bb61f,0x3a2f3bd9,
0xb9a80000,0xb9a8bc00,0x39a80000,0x39a83c00,0xbbf6b9a8,0xb4a5baa7,0x3b0e361f,0x39133bd9,0xbaa7bc00,0x323eb61f,0x3bd939a8,0x38723b64,0xb4a5b9a8,0x3913323e,0x3bf63b64,0x378b3aa7,
0x361f0000,0x3b6439a8,0x3b643c00,0x361f39a8,0x3b0e39a8,0x3bf63bd9,0x3a2f3b64,0x34a53872,0x3bd93c00,0x3aa73b64,0x387239a8,0x323e361f,0x391339a8,0x378b3872,0x34a5361f,0x2e46323e,
0x3f803f80,0x3f803f80,0x3f803f80,0x3f803f80,0x3f7f3f80,0x3f753f7b,0x3f623f6d,0x3f463f55,0x3f7b3f80,0x3f553f6d,0x3f0e3f35,0x3e483ec4,0x3f753f80,0x3f223f55,0x3dc93ec4,0xbef1be48,
0x3f6d3f80,0x3ec43f35,0xbec40000,0xbf6dbf35,0x3f623f80,0x3dc93f0e,0xbf46bec4,0xbf75bf7b,0x3f553f80,0xbe483ec4,0xbf7bbf35,0xbf0ebf6d,0x3f463f80,0xbef13e48,0xbf75bf6d,0x3dc9bf0e,
0x3f353f80,0xbf350000,0xbf35bf80,0x3f350000,0x3f223f80,0xbf62be48,0xbe95bf6d,0x3f7f3f0e,0x3f0e3f80,0xbf7bbec4,0x3e48bf35,0x3f553f6d,0x3ef13f80,0xbf7fbf0e,0x3f22bec4,0x3e953f7b,
0x3ec43f80,0xbf6dbf35,0x3f6d0000,0xbec43f35,0x3e953f80,0xbf46bf55,0x3f7f3ec4,0xbf623e48,0x3e483f80,0xbf0ebf6d,0x3f553f35,0xbf7bbec4,0x3dc93f80,0xbe95bf7b,0x3ef13f6d,0xbf22bf55,
0x3f80,0xbf80,0x3f80,0xbf80,0xbdc93f80,0x3e95bf7b,0xbef13f6d,0x3f22bf55,0xbe483f80,0x3f0ebf6d,0xbf553f35,0x3f7bbec4,0xbe953f80,0x3f46bf55,0xbf7f3ec4,0x3f623e48,
0xbec43f80,0x3f6dbf35,0xbf6d0000,0x3ec43f35,0xbef13f80,0x3f7fbf0e,0xbf22bec4,0xbe953f7b,0xbf0e3f80,0x3f7bbec4,0xbe48bf35,0xbf553f6d,0xbf223f80,0x3f62be48,0x3e95bf6d,0xbf7f3f0e,
0xbf353f80,0x3f350000,0x3f35bf80,0xbf350000,0xbf463f80,0x3ef13e48,0x3f75bf6d,0xbdc9bf0e,0xbf553f80,0x3e483ec4,0x3f7bbf35,0x3f0ebf6d,0xbf623f80,0xbdc93f0e,0x3f46bec4,0x3f75bf7b,
0xbf6d3f80,0xbec43f35,0x3ec40000,0x3f6dbf35,0xbf753f80,0xbf223f55,0xbdc93ec4,0x3ef1be48,0xbf7b3f80,0xbf553f6d,0xbf0e3f35,0xbe483ec4,0xbf7f3f80,0xbf753f7b,0xbf623f6d,0xbf463f55,
0xbf803f80,0xbf803f80,0xbf803f80,0xbf803f80,0xbf7f3f80,0xbf753f7b,0xbf623f6d,0xbf463f55,0xbf7b3f80,0xbf553f6d,0xbf0e3f35,0xbe483ec4,0xbf753f80,0xbf223f55,0xbdc93ec4,0x3ef1be48,
0xbf6d3f80,0xbec43f35,0x3ec40000,0x3f6dbf35,0xbf623f80,0xbdc93f0e,0x3f46bec4,0x3f75bf7b,0xbf553f80,0x3e483ec4,0x3f7bbf35,0x3f0ebf6d,0xbf463f80,0x3ef13e48,0x3f75bf6d,0xbdc9bf0e,
0xbf353f80,0x3f350000,0x3f35bf80,0xbf350000,0xbf223f80,0x3f62be48,0x3e95bf6d,0xbf7f3f0e,0xbf0e3f80,0x3f7bbec4,0xbe48bf35,0xbf553f6d,0xbef13f80,0x3f7fbf0e,0xbf22bec4,0xbe953f7b,
0xbec43f80,0x3f6dbf35,0xbf6d0000,0x3ec43f35,0xbe953f80,0x3f46bf55,0xbf7f3ec4,0x3f623e48,0xbe483f80,0x3f0ebf6d,0xbf553f35,0x3f7bbec4,0xbdc93f80,0x3e95bf7b,0xbef13f6d,0x3f22bf55,
0x3f80,0xbf80,0x3f80,0xbf80,0x3dc93f80,0xbe95bf7b,0x3ef13f6d,0xbf22bf55,0x3e483f80,0xbf0ebf6d,0x3f553f35,0xbf7bbec4,0x3e953f80,0xbf46bf55,0x3f7f3ec4,0xbf623e48,
0x3ec43f80,0xbf6dbf35,0x3f6d0000,0xbec43f35,0x3ef13f80,0xbf7fbf0e,0x3f22bec4,0x3e953f7b,0x3f0e3f80,0xbf7bbec4,0x3e48bf35,0x3f553f6d,0x3f223f80,0xbf62be48,0xbe95bf6d,0x3f7f3f0e,
0x3f353f80,0xbf350000,0xbf35bf80,0x3f350000,0x3f463f80,0xbef13e48,0xbf75bf6d,0x3dc9bf0e,0x3f553f80,0xbe483ec4,0xbf7bbf35,0xbf0ebf6d,0x3f623f80,0x3dc93f0e,0xbf46bec4,0xbf75bf7b,
0x3f6d3f80,0x3ec43f35,0xbec40000,0xbf6dbf35,0x3f753f80,0x3f223f55,0x3dc93ec4,0xbef1be48,0x3f7b3f80,0x3f553f6d,0x3f0e3f35,0x3e483ec4,0x3f7f3f80,0x3f753f7b,0x3f623f6d,0x3f463f55,
0,0,0,0,0x3dc90000,0x3e953e48,0x3ef13ec4,0x3f223f0e,0x3e480000,0x3f0e3ec4,0x3f553f35,0x3f7b3f6d,0x3e950000,0x3f463f0e,0x3f7f3f6d,0x3f623f7b,
0x3ec40000,0x3f6d3f35,0x3f6d3f80,0x3ec43f35,0x3ef10000,0x3f7f3f55,0x3f223f6d,0xbe953e48,0x3f0e0000,0x3f7b3f6d,0x3e483f35,0xbf55bec4,0x3f220000,0x3f623f7b,0xbe953ec4,0xbf7fbf55,
0x3f350000,0x3f353f80,0xbf350000,0xbf35bf80,0x3f460000,0x3ef13f7b,0xbf75bec4,0xbdc9bf55,0x3f550000,0x3e483f6d,0xbf7bbf35,0x3f0ebec4,0x3f620000,0xbdc93f55,0xbf46bf6d,0x3f753e48,
0x3f6d0000,0xbec43f35,0xbec4bf80,0x3f6d3f35,0x3f750000,0xbf223f0e,0x3dc9bf6d,0x3ef13f7b,0x3f7b0000,0xbf553ec4,0x3f0ebf35,0xbe483f6d,0x3f7f0000,0xbf753e48,0x3f62bec4,0xbf463f0e,
0x3f800000,0xbf800000,0x3f800000,0xbf800000,0x3f7f0000,0xbf75be48,0x3f623ec4,0xbf46bf0e,0x3f7b0000,0xbf55bec4,0x3f0e3f35,0xbe48bf6d,0x3f750000,0xbf22bf0e,0x3dc93f6d,0x3ef1bf7b,
0x3f6d0000,0xbec4bf35,0xbec43f80,0x3f6dbf35,0x3f620000,0xbdc9bf55,0xbf463f6d,0x3f75be48,0x3f550000,0x3e48bf6d,0xbf7b3f35,0x3f0e3ec4,0x3f460000,0x3ef1bf7b,0xbf753ec4,0xbdc93f55,
0x3f350000,0x3f35bf80,0xbf350000,0xbf353f80,0x3f220000,0x3f62bf7b,0xbe95bec4,0xbf7f3f55,0x3f0e0000,0x3f7bbf6d,0x3e48bf35,0xbf553ec4,0x3ef10000,0x3f7fbf55,0x3f22bf6d,0xbe95be48,
0x3ec40000,0x3f6dbf35,0x3f6dbf80,0x3ec4bf35,0x3e950000,0x3f46bf0e,0x3f7fbf6d,0x3f62bf7b,0x3e480000,0x3f0ebec4,0x3f55bf35,0x3f7bbf6d,0x3dc90000,0x3e95be48,0x3ef1bec4,0x3f22bf0e,
0,0,0,0,0xbdc90000,0xbe953e48,0xbef13ec4,0xbf223f0e,0xbe480000,0xbf0e3ec4,0xbf553f35,0xbf7b3f6d,0xbe950000,0xbf463f0e,0xbf7f3f6d,0xbf623f7b,
0xbec40000,0xbf6d3f35,0xbf6d3f80,0xbec43f35,0xbef10000,0xbf7f3f55,0xbf223f6d,0x3e953e48,0xbf0e0000,0xbf7b3f6d,0xbe483f35,0x3f55bec4,0xbf220000,0xbf623f7b,0x3e953ec4,0x3f7fbf55,
0xbf350000,0xbf353f80,0x3f350000,0x3f35bf80,0xbf460000,0xbef13f7b,0x3f75bec4,0x3dc9bf55,0xbf550000,0xbe483f6d,0x3f7bbf35,0xbf0ebec4,0xbf620000,0x3dc93f55,0x3f46bf6d,0xbf753e48,
0xbf6d0000,0x3ec43f35,0x3ec4bf80,0xbf6d3f35,0xbf750000,0x3f223f0e,0xbdc9bf6d,0xbef13f7b,0xbf7b0000,0x3f553ec4,0xbf0ebf35,0x3e483f6d,0xbf7f0000,0x3f753e48,0xbf62bec4,0x3f463f0e,
0xbf800000,0x3f800000,0xbf800000,0x3f800000,0xbf7f0000,0x3f75be48,0xbf623ec4,0x3f46bf0e,0xbf7b0000,0x3f55bec4,0xbf0e3f35,0x3e48bf6d,0xbf750000,0x3f22bf0e,0xbdc93f6d,0xbef1bf7b,
0xbf6d0000,0x3ec4bf35,0x3ec43f80,0xbf6dbf35,0xbf620000,0x3dc9bf55,0x3f463f6d,0xbf75be48,0xbf550000,0xbe48bf6d,0x3f7b3f35,0xbf0e3ec4,0xbf460000,0xbef1bf7b,0x3f753ec4,0x3dc93f55,
0xbf350000,0xbf35bf80,0x3f350000,0x3f353f80,0xbf220000,0xbf62bf7b,0x3e95bec4,0x3f7f3f55,0xbf0e0000,0xbf7bbf6d,0xbe48bf35,0x3f553ec4,0xbef10000,0xbf7fbf55,0xbf22bf6d,0x3e95be48,
0xbec40000,0xbf6dbf35,0xbf6dbf80,0xbec4bf35,0xbe950000,0xbf46bf0e,0xbf7fbf6d,0xbf62bf7b,0xbe480000,0xbf0ebec4,0xbf55bf35,0xbf7bbf6d,0xbdc90000,0xbe95be48,0xbef1bec4,0xbf22bf0e,
0x3f803f80,0x3f803f80,0x3f803f80,0x3f803f80,0x3f223f35,0x3ef13f0e,0x3e953ec4,0x3dc93e48,0xbe480000,0xbf0ebec4,0xbf55bf35,0xbf7bbf6d,0xbf62bf35,0xbf7fbf7b,0xbf46bf6d,0xbe95bf0e,
0xbf6dbf80,0xbec4bf35,0x3ec40000,0x3f6d3f35,0xbe95bf35,0x3f223e48,0x3f7f3f6d,0x3ef13f55,0x3f0e0000,0x3f7b3f6d,0x3e483f35,0xbf55bec4,0x3f7f3f35,0x3e953f55,0xbf62bec4,0xbf22bf7b,
0x3f353f80,0xbf350000,0xbf35bf80,0x3f350000,0xbdc93f35,0xbf75bf55,0x3ef1bec4,0x3f463f7b,0xbf550000,0xbe48bf6d,0x3f7b3f35,0xbf0e3ec4,0xbf75bf35,0x3f46be48,0x3dc93f6d,0xbf62bf55,
0xbec4bf80,0x3f6d3f35,0xbf6d0000,0x3ec4bf35,0x3ef1bf35,0x3dc93f7b,0xbf22bf6d,0x3f753f0e,0x3f7b0000,0xbf553ec4,0x3f0ebf35,0xbe483f6d,0x3f463f35,0xbf62bf0e,0x3f753ec4,0xbf7fbe48,
0x3f80,0xbf80,0x3f80,0xbf80,0xbf463f35,0x3f62bf0e,0xbf753ec4,0x3f7fbe48,0xbf7b0000,0x3f553ec4,0xbf0ebf35,0x3e483f6d,0xbef1bf35,0xbdc93f7b,0x3f22bf6d,0xbf753f0e,
0x3ec4bf80,0xbf6d3f35,0x3f6d0000,0xbec4bf35,0x3f75bf35,0xbf46be48,0xbdc93f6d,0x3f62bf55,0x3f550000,0x3e48bf6d,0xbf7b3f35,0x3f0e3ec4,0x3dc93f35,0x3f75bf55,0xbef1bec4,0xbf463f7b,
0xbf353f80,0x3f350000,0x3f35bf80,0xbf350000,0xbf7f3f35,0xbe953f55,0x3f62bec4,0x3f22bf7b,0xbf0e0000,0xbf7b3f6d,0xbe483f35,0x3f55bec4,0x3e95bf35,0xbf223e48,0xbf7f3f6d,0xbef13f55,
0x3f6dbf80,0x3ec4bf35,0xbec40000,0xbf6d3f35,0x3f62bf35,0x3f7fbf7b,0x3f46bf6d,0x3e95bf0e,0x3e480000,0x3f0ebec4,0x3f55bf35,0x3f7bbf6d,0xbf223f35,0xbef13f0e,0xbe953ec4,0xbdc93e48,
0xbf803f80,0xbf803f80,0xbf803f80,0xbf803f80,0xbf223f35,0xbef13f0e,0xbe953ec4,0xbdc93e48,0x3e480000,0x3f0ebec4,0x3f55bf35,0x3f7bbf6d,0x3f62bf35,0x3f7fbf7b,0x3f46bf6d,0x3e95bf0e,
0x3f6dbf80,0x3ec4bf35,0xbec40000,0xbf6d3f35,0x3e95bf35,0xbf223e48,0xbf7f3f6d,0xbef13f55,0xbf0e0000,0xbf7b3f6d,0xbe483f35,0x3f55bec4,0xbf7f3f35,0xbe953f55,0x3f62bec4,0x3f22bf7b,
0xbf353f80,0x3f350000,0x3f35bf80,0xbf350000,0x3dc93f35,0x3f75bf55,0xbef1bec4,0xbf463f7b,0x3f550000,0x3e48bf6d,0xbf7b3f35,0x3f0e3ec4,0x3f75bf35,0xbf46be48,0xbdc93f6d,0x3f62bf55,
0x3ec4bf80,0xbf6d3f35,0x3f6d0000,0xbec4bf35,0xbef1bf35,0xbdc93f7b,0x3f22bf6d,0xbf753f0e,0xbf7b0000,0x3f553ec4,0xbf0ebf35,0x3e483f6d,0xbf463f35,0x3f62bf0e,0xbf753ec4,0x3f7fbe48,
0x3f80,0xbf80,0x3f80,0xbf80,0x3f463f35,0xbf62bf0e,0x3f753ec4,0xbf7fbe48,0x3f7b0000,0xbf553ec4,0x3f0ebf35,0xbe483f6d,0x3ef1bf35,0x3dc93f7b,0xbf22bf6d,0x3f753f0e,
0xbec4bf80,0x3f6d3f35,0xbf6d0000,0x3ec4bf35,0xbf75bf35,0x3f46be48,0x3dc93f6d,0xbf62bf55,0xbf550000,0xbe48bf6d,0x3f7b3f35,0xbf0e3ec4,0xbdc93f35,0xbf75bf55,0x3ef1bec4,0x3f463f7b,
0x3f353f80,0xbf350000,0xbf35bf80,0x3f350000,0x3f7f3f35,0x3e953f55,0xbf62bec4,0xbf22bf7b,0x3f0e0000,0x3f7b3f6d,0x3e483f35,0xbf55bec4,0xbe95bf35,0x3f223e48,0x3f7f3f6d,0x3ef13f55,
0xbf6dbf80,0xbec4bf35,0x3ec40000,0x3f6d3f35,0xbf62bf35,0xbf7fbf7b,0xbf46bf6d,0xbe95bf0e,0xbe480000,0xbf0ebec4,0xbf55bf35,0xbf7bbf6d,0x3f223f35,0x3ef13f0e,0x3e953ec4,0x3dc93e48,
0,0,0,0,0x3f463f35,0x3f623f55,0x3f753f6d,0x3f7f3f7b,0x3f7b3f80,0x3f553f6d,0x3f0e3f35,0x3e483ec4,0x3ef13f35,0xbdc93e48,0xbf22bec4,0xbf75bf55,
0xbec40000,0xbf6dbf35,0xbf6dbf80,0xbec4bf35,0xbf75bf35,0xbf46bf7b,0x3dc9bec4,0x3f623f0e,0xbf55bf80,0x3e48bec4,0x3f7b3f35,0x3f0e3f6d,0xbdc9bf35,0x3f753f0e,0x3ef13f6d,0xbf46be48,
0x3f350000,0x3f353f80,0xbf350000,0xbf35bf80,0x3f7f3f35,0xbe953f0e,0xbf62bf6d,0x3f22be48,0x3f0e3f80,0xbf7bbec4,0x3e48bf35,0x3f553f6d,0xbe953f35,0xbf22bf7b,0x3f7f3ec4,0xbef13f0e,
0xbf6d0000,0x3ec4bf35,0x3ec43f80,0xbf6dbf35,0xbf62bf35,0x3f7f3e48,0xbf463ec4,0x3e95bf55,0xbe48bf80,0x3f0e3f6d,0xbf55bf35,0x3f7b3ec4,0x3f22bf35,0xbef13f55,0x3e95bf6d,0xbdc93f7b,
0x3f800000,0xbf800000,0x3f800000,0xbf800000,0x3f223f35,0xbef1bf55,0x3e953f6d,0xbdc9bf7b,0xbe483f80,0x3f0ebf6d,0xbf553f35,0x3f7bbec4,0xbf623f35,0x3f7fbe48,0xbf46bec4,0x3e953f55,
0xbf6d0000,0x3ec43f35,0x3ec4bf80,0xbf6d3f35,0xbe95bf35,0xbf223f7b,0x3f7fbec4,0xbef1bf0e,0x3f0ebf80,0xbf7b3ec4,0x3e483f35,0x3f55bf6d,0x3f7fbf35,0xbe95bf0e,0xbf623f6d,0x3f223e48,
0x3f350000,0x3f35bf80,0xbf350000,0xbf353f80,0xbdc93f35,0x3f75bf0e,0x3ef1bf6d,0xbf463e48,0xbf553f80,0x3e483ec4,0x3f7bbf35,0x3f0ebf6d,0xbf753f35,0xbf463f7b,0x3dc93ec4,0x3f62bf0e,
0xbec40000,0xbf6d3f35,0xbf6d3f80,0xbec43f35,0x3ef1bf35,0xbdc9be48,0xbf223ec4,0xbf753f55,0x3f7bbf80,0x3f55bf6d,0x3f0ebf35,0x3e48bec4,0x3f46bf35,0x3f62bf55,0x3f75bf6d,0x3f7fbf7b,
0,0,0,0,0xbf463f35,0xbf623f55,0xbf753f6d,0xbf7f3f7b,0xbf7b3f80,0xbf553f6d,0xbf0e3f35,0xbe483ec4,0xbef13f35,0x3dc93e48,0x3f22bec4,0x3f75bf55,
0x3ec40000,0x3f6dbf35,0x3f6dbf80,0x3ec4bf35,0x3f75bf35,0x3f46bf7b,0xbdc9bec4,0xbf623f0e,0x3f55bf80,0xbe48bec4,0xbf7b3f35,0xbf0e3f6d,0x3dc9bf35,0xbf753f0e,0xbef13f6d,0x3f46be48,
0xbf350000,0xbf353f80,0x3f350000,0x3f35bf80,0xbf7f3f35,0x3e953f0e,0x3f62bf6d,0xbf22be48,0xbf0e3f80,0x3f7bbec4,0xbe48bf35,0xbf553f6d,0x3e953f35,0x3f22bf7b,0xbf7f3ec4,0x3ef13f0e,
0x3f6d0000,0xbec4bf35,0xbec43f80,0x3f6dbf35,0x3f62bf35,0xbf7f3e48,0x3f463ec4,0xbe95bf55,0x3e48bf80,0xbf0e3f6d,0x3f55bf35,0xbf7b3ec4,0xbf22bf35,0x3ef13f55,0xbe95bf6d,0x3dc93f7b,
0xbf800000,0x3f800000,0xbf800000,0x3f800000,0xbf223f35,0x3ef1bf55,0xbe953f6d,0x3dc9bf7b,0x3e483f80,0xbf0ebf6d,0x3f553f35,0xbf7bbec4,0x3f623f35,0xbf7fbe48,0x3f46bec4,0xbe953f55,
0x3f6d0000,0xbec43f35,0xbec4bf80,0x3f6d3f35,0x3e95bf35,0x3f223f7b,0xbf7fbec4,0x3ef1bf0e,0xbf0ebf80,0x3f7b3ec4,0xbe483f35,0xbf55bf6d,0xbf7fbf35,0x3e95bf0e,0x3f623f6d,0xbf223e48,
0xbf350000,0xbf35bf80,0x3f350000,0x3f353f80,0x3dc93f35,0xbf75bf0e,0xbef1bf6d,0x3f463e48,0x3f553f80,0xbe483ec4,0xbf7bbf35,0xbf0ebf6d,0x3f753f35,0x3f463f7b,0xbdc93ec4,0xbf62bf0e,
0x3ec40000,0x3f6d3f35,0x3f6d3f80,0x3ec43f35,0xbef1bf35,0x3dc9be48,0x3f223ec4,0x3f753f55,0xbf7bbf80,0xbf55bf6d,0xbf0ebf35,0xbe48bec4,0xbf46bf35,0xbf62bf55,0xbf75bf6d,0xbf7fbf7b,
0x3f803f80,0x3f803f80,0x3f803f80,0x3f803f80,0xbdc90000,0xbe95be48,0xbef1bec4,0xbf22bf0e,0xbf7bbf80,0xbf55bf6d,0xbf0ebf35,0xbe48bec4,0x3e950000,0x3f463f0e,0x3f7f3f6d,0x3f623f7b,
0x3f6d3f80,0x3ec43f35,0xbec40000,0xbf6dbf35,0xbef10000,0xbf7fbf55,0xbf22bf6d,0x3e95be48,0xbf55bf80,0x3e48bec4,0x3f7b3f35,0x3f0e3f6d,0x3f220000,0x3f623f7b,0xbe953ec4,0xbf7fbf55,
0x3f353f80,0xbf350000,0xbf35bf80,0x3f350000,0xbf460000,0xbef1bf7b,0x3f753ec4,0x3dc93f55,0xbf0ebf80,0x3f7b3ec4,0xbe483f35,0xbf55bf6d,0x3f620000,0xbdc93f55,0xbf46bf6d,0x3f753e48,
0x3ec43f80,0xbf6dbf35,0x3f6d0000,0xbec43f35,0xbf750000,0x3f22bf0e,0xbdc93f6d,0xbef1bf7b,0xbe48bf80,0x3f0e3f6d,0xbf55bf35,0x3f7b3ec4,0x3f7f0000,0xbf753e48,0x3f62bec4,0xbf463f0e,
0x3f80,0xbf80,0x3f80,0xbf80,0xbf7f0000,0x3f753e48,0xbf62bec4,0x3f463f0e,0x3e48bf80,0xbf0e3f6d,0x3f55bf35,0xbf7b3ec4,0x3f750000,0xbf22bf0e,0x3dc93f6d,0x3ef1bf7b,
0xbec43f80,0x3f6dbf35,0xbf6d0000,0x3ec43f35,0xbf620000,0x3dc93f55,0x3f46bf6d,0xbf753e48,0x3f0ebf80,0xbf7b3ec4,0x3e483f35,0x3f55bf6d,0x3f460000,0x3ef1bf7b,0xbf753ec4,0xbdc93f55,
0xbf353f80,0x3f350000,0x3f35bf80,0xbf350000,0xbf220000,0xbf623f7b,0x3e953ec4,0x3f7fbf55,0x3f55bf80,0xbe48bec4,0xbf7b3f35,0xbf0e3f6d,0x3ef10000,0x3f7fbf55,0x3f22bf6d,0xbe95be48,
0xbf6d3f80,0xbec43f35,0x3ec40000,0x3f6dbf35,0xbe950000,0xbf463f0e,0xbf7f3f6d,0xbf623f7b,0x3f7bbf80,0x3f55bf6d,0x3f0ebf35,0x3e48bec4,0x3dc90000,0x3e95be48,0x3ef1bec4,0x3f22bf0e,
0xbf803f80,0xbf803f80,0xbf803f80,0xbf803f80,0x3dc90000,0x3e95be48,0x3ef1bec4,0x3f22bf0e,0x3f7bbf80,0x3f55bf6d,0x3f0ebf35,0x3e48bec4,0xbe950000,0xbf463f0e,0xbf7f3f6d,0xbf623f7b,
0xbf6d3f80,0xbec43f35,0x3ec40000,0x3f6dbf35,0x3ef10000,0x3f7fbf55,0x3f22bf6d,0xbe95be48,0x3f55bf80,0xbe48bec4,0xbf7b3f35,0xbf0e3f6d,0xbf220000,0xbf623f7b,0x3e953ec4,0x3f7fbf55,
0xbf353f80,0x3f350000,0x3f35bf80,0xbf350000,0x3f460000,0x3ef1bf7b,0xbf753ec4,0xbdc93f55,0x3f0ebf80,0xbf7b3ec4,0x3e483f35,0x3f55bf6d,0xbf620000,0x3dc93f55,0x3f46bf6d,0xbf753e48,
0xbec43f80,0x3f6dbf35,0xbf6d0000,0x3ec43f35,0x3f750000,0xbf22bf0e,0x3dc93f6d,0x3ef1bf7b,0x3e48bf80,0xbf0e3f6d,0x3f55bf35,0xbf7b3ec4,0xbf7f0000,0x3f753e48,0xbf62bec4,0x3f463f0e,
0x3f80,0xbf80,0x3f80,0xbf80,0x3f7f0000,0xbf753e48,0x3f62bec4,0xbf463f0e,0xbe48bf80,0x3f0e3f6d,0xbf55bf35,0x3f7b3ec4,0xbf750000,0x3f22bf0e,0xbdc93f6d,0xbef1bf7b,
0x3ec43f80,0xbf6dbf35,0x3f6d0000,0xbec43f35,0x3f620000,0xbdc93f55,0xbf46bf6d,0x3f753e48,0xbf0ebf80,0x3f7b3ec4,0xbe483f35,0xbf55bf6d,0xbf460000,0xbef1bf7b,0x3f753ec4,0x3dc93f55,
0x3f353f80,0xbf350000,0xbf35bf80,0x3f350000,0x3f220000,0x3f623f7b,0xbe953ec4,0xbf7fbf55,0xbf55bf80,0x3e48bec4,0x3f7b3f35,0x3f0e3f6d,0xbef10000,0xbf7fbf55,0xbf22bf6d,0x3e95be48,
0x3f6d3f80,0x3ec43f35,0xbec40000,0xbf6dbf35,0x3e950000,0x3f463f0e,0x3f7f3f6d,0x3f623f7b,0xbf7bbf80,0xbf55bf6d,0xbf0ebf35,0xbe48bec4,0xbdc90000,0xbe95be48,0xbef1bec4,0xbf22bf0e,
0,0,0,0,0x3f7f3f80,0x3f753f7b,0x3f623f6d,0x3f463f55,0xbe480000,0xbf0ebec4,0xbf55bf35,0xbf7bbf6d,0xbf75bf80,0xbf22bf55,0xbdc9bec4,0x3ef13e48,
0x3ec40000,0x3f6d3f35,0x3f6d3f80,0x3ec43f35,0x3f623f80,0x3dc93f0e,0xbf46bec4,0xbf75bf7b,0xbf0e0000,0xbf7bbf6d,0xbe48bf35,0x3f553ec4,0xbf46bf80,0x3ef1be48,0x3f753f6d,0xbdc93f0e,
0x3f350000,0x3f353f80,0xbf350000,0xbf35bf80,0x3f223f80,0xbf62be48,0xbe95bf6d,0x3f7f3f0e,0xbf550000,0xbe48bf6d,0x3f7b3f35,0xbf0e3ec4,0xbef1bf80,0x3f7f3f0e,0xbf223ec4,0xbe95bf7b,
0x3f6d0000,0xbec43f35,0xbec4bf80,0x3f6d3f35,0x3e953f80,0xbf46bf55,0x3f7f3ec4,0xbf623e48,0xbf7b0000,0x3f55bec4,0xbf0e3f35,0x3e48bf6d,0xbdc9bf80,0x3e953f7b,0xbef1bf6d,0x3f223f55,
0x3f800000,0xbf800000,0x3f800000,0xbf800000,0xbdc93f80,0x3e95bf7b,0xbef13f6d,0x3f22bf55,0xbf7b0000,0x3f553ec4,0xbf0ebf35,0x3e483f6d,0x3e95bf80,0xbf463f55,0x3f7fbec4,0xbf62be48,
0x3f6d0000,0xbec4bf35,0xbec43f80,0x3f6dbf35,0xbef13f80,0x3f7fbf0e,0xbf22bec4,0xbe953f7b,0xbf550000,0xbe483f6d,0x3f7bbf35,0xbf0ebec4,0x3f22bf80,0xbf623e48,0xbe953f6d,0x3f7fbf0e,
0x3f350000,0x3f35bf80,0xbf350000,0xbf353f80,0xbf463f80,0x3ef13e48,0x3f75bf6d,0xbdc9bf0e,0xbf0e0000,0xbf7b3f6d,0xbe483f35,0x3f55bec4,0x3f62bf80,0x3dc9bf0e,0xbf463ec4,0xbf753f7b,
0x3ec40000,0x3f6dbf35,0x3f6dbf80,0x3ec4bf35,0xbf753f80,0xbf223f55,0xbdc93ec4,0x3ef1be48,0xbe480000,0xbf0e3ec4,0xbf553f35,0xbf7b3f6d,0x3f7fbf80,0x3f75bf7b,0x3f62bf6d,0x3f46bf55,
0,0,0,0,0xbf7f3f80,0xbf753f7b,0xbf623f6d,0xbf463f55,0x3e480000,0x3f0ebec4,0x3f55bf35,0x3f7bbf6d,0x3f75bf80,0x3f22bf55,0x3dc9bec4,0xbef13e48,
0xbec40000,0xbf6d3f35,0xbf6d3f80,0xbec43f35,0xbf623f80,0xbdc93f0e,0x3f46bec4,0x3f75bf7b,0x3f0e0000,0x3f7bbf6d,0x3e48bf35,0xbf553ec4,0x3f46bf80,0xbef1be48,0xbf753f6d,0x3dc93f0e,
0xbf350000,0xbf353f80,0x3f350000,0x3f35bf80,0xbf223f80,0x3f62be48,0x3e95bf6d,0xbf7f3f0e,0x3f550000,0x3e48bf6d,0xbf7b3f35,0x3f0e3ec4,0x3ef1bf80,0xbf7f3f0e,0x3f223ec4,0x3e95bf7b,
0xbf6d0000,0x3ec43f35,0x3ec4bf80,0xbf6d3f35,0xbe953f80,0x3f46bf55,0xbf7f3ec4,0x3f623e48,0x3f7b0000,0xbf55bec4,0x3f0e3f35,0xbe48bf6d,0x3dc9bf80,0xbe953f7b,0x3ef1bf6d,0xbf223f55,
0xbf800000,0x3f800000,0xbf800000,0x3f800000,0x3dc93f80,0xbe95bf7b,0x3ef13f6d,0xbf22bf55,0x3f7b0000,0xbf553ec4,0x3f0ebf35,0xbe483f6d,0xbe95bf80,0x3f463f55,0xbf7fbec4,0x3f62be48,
0xbf6d0000,0x3ec4bf35,0x3ec43f80,0xbf6dbf35,0x3ef13f80,0xbf7fbf0e,0x3f22bec4,0x3e953f7b,0x3f550000,0x3e483f6d,0xbf7bbf35,0x3f0ebec4,0xbf22bf80,0x3f623e48,0x3e953f6d,0xbf7fbf0e,
0xbf350000,0xbf35bf80,0x3f350000,0x3f353f80,0x3f463f80,0xbef13e48,0xbf75bf6d,0x3dc9bf0e,0x3f0e0000,0x3f7b3f6d,0x3e483f35,0xbf55bec4,0xbf62bf80,0xbdc9bf0e,0x3f463ec4,0x3f753f7b,
0xbec40000,0xbf6dbf35,0xbf6dbf80,0xbec4bf35,0x3f753f80,0x3f223f55,0x3dc93ec4,0xbef1be48,0x3e480000,0x3f0e3ec4,0x3f553f35,0x3f7b3f6d,0xbf7fbf80,0xbf75bf7b,0xbf62bf6d,0xbf46bf55,
0x3f803f80,0x3f803f80,0x3f803f80,0x3f803f80,0xbf46bf35,0xbf62bf55,0xbf75bf6d,0xbf7fbf7b,0x3e480000,0x3f0e3ec4,0x3f553f35,0x3f7b3f6d,0x3ef13f35,0xbdc93e48,0xbf22bec4,0xbf75bf55,
0xbf6dbf80,0xbec4bf35,0x3ec40000,0x3f6d3f35,0x3f753f35,0x3f463f7b,0xbdc93ec4,0xbf62bf0e,0xbf0e0000,0xbf7bbf6d,0xbe48bf35,0x3f553ec4,0xbdc9bf35,0x3f753f0e,0x3ef13f6d,0xbf46be48,
0x3f353f80,0xbf350000,0xbf35bf80,0x3f350000,0xbf7fbf35,0x3e95bf0e,0x3f623f6d,0xbf223e48,0x3f550000,0x3e483f6d,0xbf7bbf35,0x3f0ebec4,0xbe953f35,0xbf22bf7b,0x3f7f3ec4,0xbef13f0e,
0xbec4bf80,0x3f6d3f35,0xbf6d0000,0x3ec4bf35,0x3f623f35,0xbf7fbe48,0x3f46bec4,0xbe953f55,0xbf7b0000,0x3f55bec4,0xbf0e3f35,0x3e48bf6d,0x3f22bf35,0xbef13f55,0x3e95bf6d,0xbdc93f7b,
0x3f80,0xbf80,0x3f80,0xbf80,0xbf22bf35,0x3ef13f55,0xbe95bf6d,0x3dc93f7b,0x3f7b0000,0xbf55bec4,0x3f0e3f35,0xbe48bf6d,0xbf623f35,0x3f7fbe48,0xbf46bec4,0x3e953f55,
0x3ec4bf80,0xbf6d3f35,0x3f6d0000,0xbec4bf35,0x3e953f35,0x3f22bf7b,0xbf7f3ec4,0x3ef13f0e,0xbf550000,0xbe483f6d,0x3f7bbf35,0xbf0ebec4,0x3f7fbf35,0xbe95bf0e,0xbf623f6d,0x3f223e48,
0xbf353f80,0x3f350000,0x3f35bf80,0xbf350000,0x3dc9bf35,0xbf753f0e,0xbef13f6d,0x3f46be48,0x3f0e0000,0x3f7bbf6d,0x3e48bf35,0xbf553ec4,0xbf753f35,0xbf463f7b,0x3dc93ec4,0x3f62bf0e,
0x3f6dbf80,0x3ec4bf35,0xbec40000,0xbf6d3f35,0xbef13f35,0x3dc93e48,0x3f22bec4,0x3f75bf55,0xbe480000,0xbf0e3ec4,0xbf553f35,0xbf7b3f6d,0x3f46bf35,0x3f62bf55,0x3f75bf6d,0x3f7fbf7b,
0xbf803f80,0xbf803f80,0xbf803f80,0xbf803f80,0x3f46bf35,0x3f62bf55,0x3f75bf6d,0x3f7fbf7b,0xbe480000,0xbf0e3ec4,0xbf553f35,0xbf7b3f6d,0xbef13f35,0x3dc93e48,0x3f22bec4,0x3f75bf55,
0x3f6dbf80,0x3ec4bf35,0xbec40000,0xbf6d3f35,0xbf753f35,0xbf463f7b,0x3dc93ec4,0x3f62bf0e,0x3f0e0000,0x3f7bbf6d,0x3e48bf35,0xbf553ec4,0x3dc9bf35,0xbf753f0e,0xbef13f6d,0x3f46be48,
0xbf353f80,0x3f350000,0x3f35bf80,0xbf350000,0x3f7fbf35,0xbe95bf0e,0xbf623f6d,0x3f223e48,0xbf550000,0xbe483f6d,0x3f7bbf35,0xbf0ebec4,0x3e953f35,0x3f22bf7b,0xbf7f3ec4,0x3ef13f0e,
0x3ec4bf80,0xbf6d3f35,0x3f6d0000,0xbec4bf35,0xbf623f35,0x3f7fbe48,0xbf46bec4,0x3e953f55,0x3f7b0000,0xbf55bec4,0x3f0e3f35,0xbe48bf6d,0xbf22bf35,0x3ef13f55,0xbe95bf6d,0x3dc93f7b,
0x3f80,0xbf80,0x3f80,0xbf80,0x3f22bf35,0xbef13f55,0x3e95bf6d,0xbdc93f7b,0xbf7b0000,0x3f55bec4,0xbf0e3f35,0x3e48bf6d,0x3f623f35,0xbf7fbe48,0x3f46bec4,0xbe953f55,
0xbec4bf80,0x3f6d3f35,0xbf6d0000,0x3ec4bf35,0xbe953f35,0xbf22bf7b,0x3f7f3ec4,0xbef13f0e,0x3f550000,0x3e483f6d,0xbf7bbf35,0x3f0ebec4,0xbf7fbf35,0x3e95bf0e,0x3f623f6d,0xbf223e48,
0x3f353f80,0xbf350000,0xbf35bf80,0x3f350000,0xbdc9bf35,0x3f753f0e,0x3ef13f6d,0xbf46be48,0xbf0e0000,0xbf7bbf6d,0xbe48bf35,0x3f553ec4,0x3f753f35,0x3f463f7b,0xbdc93ec4,0xbf62bf0e,
0xbf6dbf80,0xbec4bf35,0x3ec40000,0x3f6d3f35,0x3ef13f35,0xbdc93e48,0xbf22bec4,0xbf75bf55,0x3e480000,0x3f0e3ec4,0x3f553f35,0x3f7b3f6d,0xbf46bf35,0xbf62bf55,0xbf75bf6d,0xbf7fbf7b,
0,0,0,0,0x3f223f35,0x3ef13f0e,0x3e953ec4,0x3dc93e48,0xbf7bbf80,0xbf55bf6d,0xbf0ebf35,0xbe48bec4,0x3f623f35,0x3f7f3f7b,0x3f463f6d,0x3e953f0e,
0xbec40000,0xbf6dbf35,0xbf6dbf80,0xbec4bf35,0xbe95bf35,0x3f223e48,0x3f7f3f6d,0x3ef13f55,0x3f553f80,0xbe483ec4,0xbf7bbf35,0xbf0ebf6d,0xbf7fbf35,0xbe95bf55,0x3f623ec4,0x3f223f7b,
0x3f350000,0x3f353f80,0xbf350000,0xbf35bf80,0xbdc93f35,0xbf75bf55,0x3ef1bec4,0x3f463f7b,0xbf0ebf80,0x3f7b3ec4,0xbe483f35,0xbf55bf6d,0x3f753f35,0xbf463e48,0xbdc9bf6d,0x3f623f55,
0xbf6d0000,0x3ec4bf35,0x3ec43f80,0xbf6dbf35,0x3ef1bf35,0x3dc93f7b,0xbf22bf6d,0x3f753f0e,0x3e483f80,0xbf0ebf6d,0x3f553f35,0xbf7bbec4,0xbf46bf35,0x3f623f0e,0xbf75bec4,0x3f7f3e48,
0x3f800000,0xbf800000,0x3f800000,0xbf800000,0xbf463f35,0x3f62bf0e,0xbf753ec4,0x3f7fbe48,0x3e48bf80,0xbf0e3f6d,0x3f55bf35,0xbf7b3ec4,0x3ef13f35,0x3dc9bf7b,0xbf223f6d,0x3f75bf0e,
0xbf6d0000,0x3ec43f35,0x3ec4bf80,0xbf6d3f35,0x3f75bf35,0xbf46be48,0xbdc93f6d,0x3f62bf55,0xbf0e3f80,0x3f7bbec4,0xbe48bf35,0xbf553f6d,0xbdc9bf35,0xbf753f55,0x3ef13ec4,0x3f46bf7b,
0x3f350000,0x3f35bf80,0xbf350000,0xbf353f80,0xbf7f3f35,0xbe953f55,0x3f62bec4,0x3f22bf7b,0x3f55bf80,0xbe48bec4,0xbf7b3f35,0xbf0e3f6d,0xbe953f35,0x3f22be48,0x3f7fbf6d,0x3ef1bf55,
0xbec40000,0xbf6d3f35,0xbf6d3f80,0xbec43f35,0x3f62bf35,0x3f7fbf7b,0x3f46bf6d,0x3e95bf0e,0xbf7b3f80,0xbf553f6d,0xbf0e3f35,0xbe483ec4,0x3f22bf35,0x3ef1bf0e,0x3e95bec4,0x3dc9be48,
0,0,0,0,0xbf223f35,0xbef13f0e,0xbe953ec4,0xbdc93e48,0x3f7bbf80,0x3f55bf6d,0x3f0ebf35,0x3e48bec4,0xbf623f35,0xbf7f3f7b,0xbf463f6d,0xbe953f0e,
0x3ec40000,0x3f6dbf35,0x3f6dbf80,0x3ec4bf35,0x3e95bf35,0xbf223e48,0xbf7f3f6d,0xbef13f55,0xbf553f80,0x3e483ec4,0x3f7bbf35,0x3f0ebf6d,0x3f7fbf35,0x3e95bf55,0xbf623ec4,0xbf223f7b,
0xbf350000,0xbf353f80,0x3f350000,0x3f35bf80,0x3dc93f35,0x3f75bf55,0xbef1bec4,0xbf463f7b,0x3f0ebf80,0xbf7b3ec4,0x3e483f35,0x3f55bf6d,0xbf753f35,0x3f463e48,0x3dc9bf6d,0xbf623f55,
0x3f6d0000,0xbec4bf35,0xbec43f80,0x3f6dbf35,0xbef1bf35,0xbdc93f7b,0x3f22bf6d,0xbf753f0e,0xbe483f80,0x3f0ebf6d,0xbf553f35,0x3f7bbec4,0x3f46bf35,0xbf623f0e,0x3f75bec4,0xbf7f3e48,
0xbf800000,0x3f800000,0xbf800000,0x3f800000,0x3f463f35,0xbf62bf0e,0x3f753ec4,0xbf7fbe48,0xbe48bf80,0x3f0e3f6d,0xbf55bf35,0x3f7b3ec4,0xbef13f35,0xbdc9bf7b,0x3f223f6d,0xbf75bf0e,
0x3f6d0000,0xbec43f35,0xbec4bf80,0x3f6d3f35,0xbf75bf35,0x3f46be48,0x3dc93f6d,0xbf62bf55,0x3f0e3f80,0xbf7bbec4,0x3e48bf35,0x3f553f6d,0x3dc9bf35,0x3f753f55,0xbef13ec4,0xbf46bf7b,
0xbf350000,0xbf35bf80,0x3f350000,0x3f353f80,0x3f7f3f35,0x3e953f55,0xbf62bec4,0xbf22bf7b,0xbf55bf80,0x3e48bec4,0x3f7b3f35,0x3f0e3f6d,0x3e953f35,0xbf22be48,0xbf7fbf6d,0xbef1bf55,
0x3ec40000,0x3f6d3f35,0x3f6d3f80,0x3ec43f35,0xbf62bf35,0xbf7fbf7b,0xbf46bf6d,0xbe95bf0e,0x3f7b3f80,0x3f553f6d,0x3f0e3f35,0x3e483ec4,0xbf22bf35,0xbef1bf0e,0xbe95bec4,0xbdc9be48,
0x3f803f80,0x3f803f80,0x3f803f80,0x3f803f80,0xbf7fbf80,0xbf75bf7b,0xbf62bf6d,0xbf46bf55,0x3f7b3f80,0x3f553f6d,0x3f0e3f35,0x3e483ec4,0xbf75bf80,0xbf22bf55,0xbdc9bec4,0x3ef13e48,
0x3f6d3f80,0x3ec43f35,0xbec40000,0xbf6dbf35,0xbf62bf80,0xbdc9bf0e,0x3f463ec4,0x3f753f7b,0x3f553f80,0xbe483ec4,0xbf7bbf35,0xbf0ebf6d,0xbf46bf80,0x3ef1be48,0x3f753f6d,0xbdc93f0e,
0x3f353f80,0xbf350000,0xbf35bf80,0x3f350000,0xbf22bf80,0x3f623e48,0x3e953f6d,0xbf7fbf0e,0x3f0e3f80,0xbf7bbec4,0x3e48bf35,0x3f553f6d,0xbef1bf80,0x3f7f3f0e,0xbf223ec4,0xbe95bf7b,
0x3ec43f80,0xbf6dbf35,0x3f6d0000,0xbec43f35,0xbe95bf80,0x3f463f55,0xbf7fbec4,0x3f62be48,0x3e483f80,0xbf0ebf6d,0x3f553f35,0xbf7bbec4,0xbdc9bf80,0x3e953f7b,0xbef1bf6d,0x3f223f55,
0x3f80,0xbf80,0x3f80,0xbf80,0x3dc9bf80,0xbe953f7b,0x3ef1bf6d,0xbf223f55,0xbe483f80,0x3f0ebf6d,0xbf553f35,0x3f7bbec4,0x3e95bf80,0xbf463f55,0x3f7fbec4,0xbf62be48,
0xbec43f80,0x3f6dbf35,0xbf6d0000,0x3ec43f35,0x3ef1bf80,0xbf7f3f0e,0x3f223ec4,0x3e95bf7b,0xbf0e3f80,0x3f7bbec4,0xbe48bf35,0xbf553f6d,0x3f22bf80,0xbf623e48,0xbe953f6d,0x3f7fbf0e,
0xbf353f80,0x3f350000,0x3f35bf80,0xbf350000,0x3f46bf80,0xbef1be48,0xbf753f6d,0x3dc93f0e,0xbf553f80,0x3e483ec4,0x3f7bbf35,0x3f0ebf6d,0x3f62bf80,0x3dc9bf0e,0xbf463ec4,0xbf753f7b,
0xbf6d3f80,0xbec43f35,0x3ec40000,0x3f6dbf35,0x3f75bf80,0x3f22bf55,0x3dc9bec4,0xbef13e48,0xbf7b3f80,0xbf553f6d,0xbf0e3f35,0xbe483ec4,0x3f7fbf80,0x3f75bf7b,0x3f62bf6d,0x3f46bf55,
0xbf803f80,0xbf803f80,0xbf803f80,0xbf803f80,0x3f7fbf80,0x3f75bf7b,0x3f62bf6d,0x3f46bf55,0xbf7b3f80,0xbf553f6d,0xbf0e3f35,0xbe483ec4,0x3f75bf80,0x3f22bf55,0x3dc9bec4,0xbef13e48,
0xbf6d3f80,0xbec43f35,0x3ec40000,0x3f6dbf35,0x3f62bf80,0x3dc9bf0e,0xbf463ec4,0xbf753f7b,0xbf553f80,0x3e483ec4,0x3f7bbf35,0x3f0ebf6d,0x3f46bf80,0xbef1be48,0xbf753f6d,0x3dc93f0e,
0xbf353f80,0x3f350000,0x3f35bf80,0xbf350000,0x3f22bf80,0xbf623e48,0xbe953f6d,0x3f7fbf0e,0xbf0e3f80,0x3f7bbec4,0xbe48bf35,0xbf553f6d,0x3ef1bf80,0xbf7f3f0e,0x3f223ec4,0x3e95bf7b,
0xbec43f80,0x3f6dbf35,0xbf6d0000,0x3ec43f35,0x3e95bf80,0xbf463f55,0x3f7fbec4,0xbf62be48,0xbe483f80,0x3f0ebf6d,0xbf553f35,0x3f7bbec4,0x3dc9bf80,0xbe953f7b,0x3ef1bf6d,0xbf223f55,
0x3f80,0xbf80,0x3f80,0xbf80,0xbdc9bf80,0x3e953f7b,0xbef1bf6d,0x3f223f55,0x3e483f80,0xbf0ebf6d,0x3f553f35,0xbf7bbec4,0xbe95bf80,0x3f463f55,0xbf7fbec4,0x3f62be48,
0x3ec43f80,0xbf6dbf35,0x3f6d0000,0xbec43f35,0xbef1bf80,0x3f7f3f0e,0xbf223ec4,0xbe95bf7b,0x3f0e3f80,0xbf7bbec4,0x3e48bf35,0x3f553f6d,0xbf22bf80,0x3f623e48,0x3e953f6d,0xbf7fbf0e,
0x3f353f80,0xbf350000,0xbf35bf80,0x3f350000,0xbf46bf80,0x3ef1be48,0x3f753f6d,0xbdc93f0e,0x3f553f80,0xbe483ec4,0xbf7bbf35,0xbf0ebf6d,0xbf62bf80,0xbdc9bf0e,0x3f463ec4,0x3f753f7b,
0x3f6d3f80,0x3ec43f35,0xbec40000,0xbf6dbf35,0xbf75bf80,0xbf22bf55,0xbdc9bec4,0x3ef13e48,0x3f7b3f80,0x3f553f6d,0x3f0e3f35,0x3e483ec4,0xbf7fbf80,0xbf75bf7b,0xbf62bf6d,0xbf46bf55,
0,0,0,0,0xbdc90000,0xbe95be48,0xbef1bec4,0xbf22bf0e,0x3e480000,0x3f0e3ec4,0x3f553f35,0x3f7b3f6d,0xbe950000,0xbf46bf0e,0xbf7fbf6d,0xbf62bf7b,
0x3ec40000,0x3f6d3f35,0x3f6d3f80,0x3ec43f35,0xbef10000,0xbf7fbf55,0xbf22bf6d,0x3e95be48,0x3f0e0000,0x3f7b3f6d,0x3e483f35,0xbf55bec4,0xbf220000,0xbf62bf7b,0x3e95bec4,0x3f7f3f55,
0x3f350000,0x3f353f80,0xbf350000,0xbf35bf80,0xbf460000,0xbef1bf7b,0x3f753ec4,0x3dc93f55,0x3f550000,0x3e483f6d,0xbf7bbf35,0x3f0ebec4,0xbf620000,0x3dc9bf55,0x3f463f6d,0xbf75be48,
0x3f6d0000,0xbec43f35,0xbec4bf80,0x3f6d3f35,0xbf750000,0x3f22bf0e,0xbdc93f6d,0xbef1bf7b,0x3f7b0000,0xbf553ec4,0x3f0ebf35,0xbe483f6d,0xbf7f0000,0x3f75be48,0xbf623ec4,0x3f46bf0e,
0x3f800000,0xbf800000,0x3f800000,0xbf800000,0xbf7f0000,0x3f753e48,0xbf62bec4,0x3f463f0e,0x3f7b0000,0xbf55bec4,0x3f0e3f35,0xbe48bf6d,0xbf750000,0x3f223f0e,0xbdc9bf6d,0xbef13f7b,
0x3f6d0000,0xbec4bf35,0xbec43f80,0x3f6dbf35,0xbf620000,0x3dc93f55,0x3f46bf6d,0xbf753e48,0x3f550000,0x3e48bf6d,0xbf7b3f35,0x3f0e3ec4,0xbf460000,0xbef13f7b,0x3f75bec4,0x3dc9bf55,
0x3f350000,0x3f35bf80,0xbf350000,0xbf353f80,0xbf220000,0xbf623f7b,0x3e953ec4,0x3f7fbf55,0x3f0e0000,0x3f7bbf6d,0x3e48bf35,0xbf553ec4,0xbef10000,0xbf7f3f55,0xbf223f6d,0x3e953e48,
0x3ec40000,0x3f6dbf35,0x3f6dbf80,0x3ec4bf35,0xbe950000,0xbf463f0e,0xbf7f3f6d,0xbf623f7b,0x3e480000,0x3f0ebec4,0x3f55bf35,0x3f7bbf6d,0xbdc90000,0xbe953e48,0xbef13ec4,0xbf223f0e,
0,0,0,0,0x3dc90000,0x3e95be48,0x3ef1bec4,0x3f22bf0e,0xbe480000,0xbf0e3ec4,0xbf553f35,0xbf7b3f6d,0x3e950000,0x3f46bf0e,0x3f7fbf6d,0x3f62bf7b,
0xbec40000,0xbf6d3f35,0xbf6d3f80,0xbec43f35,0x3ef10000,0x3f7fbf55,0x3f22bf6d,0xbe95be48,0xbf0e0000,0xbf7b3f6d,0xbe483f35,0x3f55bec4,0x3f220000,0x3f62bf7b,0xbe95bec4,0xbf7f3f55,
0xbf350000,0xbf353f80,0x3f350000,0x3f35bf80,0x3f460000,0x3ef1bf7b,0xbf753ec4,0xbdc93f55,0xbf550000,0xbe483f6d,0x3f7bbf35,0xbf0ebec4,0x3f620000,0xbdc9bf55,0xbf463f6d,0x3f75be48,
0xbf6d0000,0x3ec43f35,0x3ec4bf80,0xbf6d3f35,0x3f750000,0xbf22bf0e,0x3dc93f6d,0x3ef1bf7b,0xbf7b0000,0x3f553ec4,0xbf0ebf35,0x3e483f6d,0x3f7f0000,0xbf75be48,0x3f623ec4,0xbf46bf0e,
0xbf800000,0x3f800000,0xbf800000,0x3f800000,0x3f7f0000,0xbf753e48,0x3f62bec4,0xbf463f0e,0xbf7b0000,0x3f55bec4,0xbf0e3f35,0x3e48bf6d,0x3f750000,0xbf223f0e,0x3dc9bf6d,0x3ef13f7b,
0xbf6d0000,0x3ec4bf35,0x3ec43f80,0xbf6dbf35,0x3f620000,0xbdc93f55,0xbf46bf6d,0x3f753e48,0xbf550000,0xbe48bf6d,0x3f7b3f35,0xbf0e3ec4,0x3f460000,0x3ef13f7b,0xbf75bec4,0xbdc9bf55,
0xbf350000,0xbf35bf80,0x3f350000,0x3f353f80,0x3f220000,0x3f623f7b,0xbe953ec4,0xbf7fbf55,0xbf0e0000,0xbf7bbf6d,0xbe48bf35,0x3f553ec4,0x3ef10000,0x3f7f3f55,0x3f223f6d,0xbe953e48,
0xbec40000,0xbf6dbf35,0xbf6dbf80,0xbec4bf35,0x3e950000,0x3f463f0e,0x3f7f3f6d,0x3f623f7b,0xbe480000,0xbf0ebec4,0xbf55bf35,0xbf7bbf6d,0x3dc90000,0x3e953e48,0x3ef13ec4,0x3f223f0e,
0x3f803f80,0x3f803f80,0x3f803f80,0x3f803f80,0xbf22bf35,0xbef1bf0e,0xbe95bec4,0xbdc9be48,0xbe480000,0xbf0ebec4,0xbf55bf35,0xbf7bbf6d,0x3f623f35,0x3f7f3f7b,0x3f463f6d,0x3e953f0e,
0xbf6dbf80,0xbec4bf35,0x3ec40000,0x3f6d3f35,0x3e953f35,0xbf22be48,0xbf7fbf6d,0xbef1bf55,0x3f0e0000,0x3f7b3f6d,0x3e483f35,0xbf55bec4,0xbf7fbf35,0xbe95bf55,0x3f623ec4,0x3f223f7b,
0x3f353f80,0xbf350000,0xbf35bf80,0x3f350000,0x3dc9bf35,0x3f753f55,0xbef13ec4,0xbf46bf7b,0xbf550000,0xbe48bf6d,0x3f7b3f35,0xbf0e3ec4,0x3f753f35,0xbf463e48,0xbdc9bf6d,0x3f623f55,
0xbec4bf80,0x3f6d3f35,0xbf6d0000,0x3ec4bf35,0xbef13f35,0xbdc9bf7b,0x3f223f6d,0xbf75bf0e,0x3f7b0000,0xbf553ec4,0x3f0ebf35,0xbe483f6d,0xbf46bf35,0x3f623f0e,0xbf75bec4,0x3f7f3e48,
0x3f80,0xbf80,0x3f80,0xbf80,0x3f46bf35,0xbf623f0e,0x3f75bec4,0xbf7f3e48,0xbf7b0000,0x3f553ec4,0xbf0ebf35,0x3e483f6d,0x3ef13f35,0x3dc9bf7b,0xbf223f6d,0x3f75bf0e,
0x3ec4bf80,0xbf6d3f35,0x3f6d0000,0xbec4bf35,0xbf753f35,0x3f463e48,0x3dc9bf6d,0xbf623f55,0x3f550000,0x3e48bf6d,0xbf7b3f35,0x3f0e3ec4,0xbdc9bf35,0xbf753f55,0x3ef13ec4,0x3f46bf7b,
0xbf353f80,0x3f350000,0x3f35bf80,0xbf350000,0x3f7fbf35,0x3e95bf55,0xbf623ec4,0xbf223f7b,0xbf0e0000,0xbf7b3f6d,0xbe483f35,0x3f55bec4,0xbe953f35,0x3f22be48,0x3f7fbf6d,0x3ef1bf55,
0x3f6dbf80,0x3ec4bf35,0xbec40000,0xbf6d3f35,0xbf623f35,0xbf7f3f7b,0xbf463f6d,0xbe953f0e,0x3e480000,0x3f0ebec4,0x3f55bf35,0x3f7bbf6d,0x3f22bf35,0x3ef1bf0e,0x3e95bec4,0x3dc9be48,
0xbf803f80,0xbf803f80,0xbf803f80,0xbf803f80,0x3f22bf35,0x3ef1bf0e,0x3e95bec4,0x3dc9be48,0x3e480000,0x3f0ebec4,0x3f55bf35,0x3f7bbf6d,0xbf623f35,0xbf7f3f7b,0xbf463f6d,0xbe953f0e,
0x3f6dbf80,0x3ec4bf35,0xbec40000,0xbf6d3f35,0xbe953f35,0x3f22be48,0x3f7fbf6d,0x3ef1bf55,0xbf0e0000,0xbf7b3f6d,0xbe483f35,0x3f55bec4,0x3f7fbf35,0x3e95bf55,0xbf623ec4,0xbf223f7b,
0xbf353f80,0x3f350000,0x3f35bf80,0xbf350000,0xbdc9bf35,0xbf753f55,0x3ef13ec4,0x3f46bf7b,0x3f550000,0x3e48bf6d,0xbf7b3f35,0x3f0e3ec4,0xbf753f35,0x3f463e48,0x3dc9bf6d,0xbf623f55,
0x3ec4bf80,0xbf6d3f35,0x3f6d0000,0xbec4bf35,0x3ef13f35,0x3dc9bf7b,0xbf223f6d,0x3f75bf0e,0xbf7b0000,0x3f553ec4,0xbf0ebf35,0x3e483f6d,0x3f46bf35,0xbf623f0e,0x3f75bec4,0xbf7f3e48,
0x3f80,0xbf80,0x3f80,0xbf80,0xbf46bf35,0x3f623f0e,0xbf75bec4,0x3f7f3e48,0x3f7b0000,0xbf553ec4,0x3f0ebf35,0xbe483f6d,0xbef13f35,0xbdc9bf7b,0x3f223f6d,0xbf75bf0e,
0xbec4bf80,0x3f6d3f35,0xbf6d0000,0x3ec4bf35,0x3f753f35,0xbf463e48,0xbdc9bf6d,0x3f623f55,0xbf550000,0xbe48bf6d,0x3f7b3f35,0xbf0e3ec4,0x3dc9bf35,0x3f753f55,0xbef13ec4,0xbf46bf7b,
0x3f353f80,0xbf350000,0xbf35bf80,0x3f350000,0xbf7fbf35,0xbe95bf55,0x3f623ec4,0x3f223f7b,0x3f0e0000,0x3f7b3f6d,0x3e483f35,0xbf55bec4,0x3e953f35,0xbf22be48,0xbf7fbf6d,0xbef1bf55,
0xbf6dbf80,0xbec4bf35,0x3ec40000,0x3f6d3f35,0x3f623f35,0x3f7f3f7b,0x3f463f6d,0x3e953f0e,0xbe480000,0xbf0ebec4,0xbf55bf35,0xbf7bbf6d,0xbf22bf35,0xbef1bf0e,0xbe95bec4,0xbdc9be48,
0,0,0,0,0xbf46bf35,0xbf62bf55,0xbf75bf6d,0xbf7fbf7b,0x3f7b3f80,0x3f553f6d,0x3f0e3f35,0x3e483ec4,0xbef1bf35,0x3dc9be48,0x3f223ec4,0x3f753f55,
0xbec40000,0xbf6dbf35,0xbf6dbf80,0xbec4bf35,0x3f753f35,0x3f463f7b,0xbdc93ec4,0xbf62bf0e,0xbf55bf80,0x3e48bec4,0x3f7b3f35,0x3f0e3f6d,0x3dc93f35,0xbf75bf0e,0xbef1bf6d,0x3f463e48,
0x3f350000,0x3f353f80,0xbf350000,0xbf35bf80,0xbf7fbf35,0x3e95bf0e,0x3f623f6d,0xbf223e48,0x3f0e3f80,0xbf7bbec4,0x3e48bf35,0x3f553f6d,0x3e95bf35,0x3f223f7b,0xbf7fbec4,0x3ef1bf0e,
0xbf6d0000,0x3ec4bf35,0x3ec43f80,0xbf6dbf35,0x3f623f35,0xbf7fbe48,0x3f46bec4,0xbe953f55,0xbe48bf80,0x3f0e3f6d,0xbf55bf35,0x3f7b3ec4,0xbf223f35,0x3ef1bf55,0xbe953f6d,0x3dc9bf7b,
0x3f800000,0xbf800000,0x3f800000,0xbf800000,0xbf22bf35,0x3ef13f55,0xbe95bf6d,0x3dc93f7b,0xbe483f80,0x3f0ebf6d,0xbf553f35,0x3f7bbec4,0x3f62bf35,0xbf7f3e48,0x3f463ec4,0xbe95bf55,
0xbf6d0000,0x3ec43f35,0x3ec4bf80,0xbf6d3f35,0x3e953f35,0x3f22bf7b,0xbf7f3ec4,0x3ef13f0e,0x3f0ebf80,0xbf7b3ec4,0x3e483f35,0x3f55bf6d,0xbf7f3f35,0x3e953f0e,0x3f62bf6d,0xbf22be48,
0x3f350000,0x3f35bf80,0xbf350000,0xbf353f80,0x3dc9bf35,0xbf753f0e,0xbef13f6d,0x3f46be48,0xbf553f80,0x3e483ec4,0x3f7bbf35,0x3f0ebf6d,0x3f75bf35,0x3f46bf7b,0xbdc9bec4,0xbf623f0e,
0xbec40000,0xbf6d3f35,0xbf6d3f80,0xbec43f35,0xbef13f35,0x3dc93e48,0x3f22bec4,0x3f75bf55,0x3f7bbf80,0x3f55bf6d,0x3f0ebf35,0x3e48bec4,0xbf463f35,0xbf623f55,0xbf753f6d,0xbf7f3f7b,
0,0,0,0,0x3f46bf35,0x3f62bf55,0x3f75bf6d,0x3f7fbf7b,0xbf7b3f80,0xbf553f6d,0xbf0e3f35,0xbe483ec4,0x3ef1bf35,0xbdc9be48,0xbf223ec4,0xbf753f55,
0x3ec40000,0x3f6dbf35,0x3f6dbf80,0x3ec4bf35,0xbf753f35,0xbf463f7b,0x3dc93ec4,0x3f62bf0e,0x3f55bf80,0xbe48bec4,0xbf7b3f35,0xbf0e3f6d,0xbdc93f35,0x3f75bf0e,0x3ef1bf6d,0xbf463e48,
0xbf350000,0xbf353f80,0x3f350000,0x3f35bf80,0x3f7fbf35,0xbe95bf0e,0xbf623f6d,0x3f223e48,0xbf0e3f80,0x3f7bbec4,0xbe48bf35,0xbf553f6d,0xbe95bf35,0xbf223f7b,0x3f7fbec4,0xbef1bf0e,
0x3f6d0000,0xbec4bf35,0xbec43f80,0x3f6dbf35,0xbf623f35,0x3f7fbe48,0xbf46bec4,0x3e953f55,0x3e48bf80,0xbf0e3f6d,0x3f55bf35,0xbf7b3ec4,0x3f223f35,0xbef1bf55,0x3e953f6d,0xbdc9bf7b,
0xbf800000,0x3f800000,0xbf800000,0x3f800000,0x3f22bf35,0xbef13f55,0x3e95bf6d,0xbdc93f7b,0x3e483f80,0xbf0ebf6d,0x3f553f35,0xbf7bbec4,0xbf62bf35,0x3f7f3e48,0xbf463ec4,0x3e95bf55,
0x3f6d0000,0xbec43f35,0xbec4bf80,0x3f6d3f35,0xbe953f35,0xbf22bf7b,0x3f7f3ec4,0xbef13f0e,0xbf0ebf80,0x3f7b3ec4,0xbe483f35,0xbf55bf6d,0x3f7f3f35,0xbe953f0e,0xbf62bf6d,0x3f22be48,
0xbf350000,0xbf35bf80,0x3f350000,0x3f353f80,0xbdc9bf35,0x3f753f0e,0x3ef13f6d,0xbf46be48,0x3f553f80,0xbe483ec4,0xbf7bbf35,0xbf0ebf6d,0xbf75bf35,0xbf46bf7b,0x3dc9bec4,0x3f623f0e,
0x3ec40000,0x3f6d3f35,0x3f6d3f80,0x3ec43f35,0x3ef13f35,0xbdc93e48,0xbf22bec4,0xbf75bf55,0xbf7bbf80,0xbf55bf6d,0xbf0ebf35,0xbe48bec4,0x3f463f35,0x3f623f55,0x3f753f6d,0x3f7f3f7b,
0x3f803f80,0x3f803f80,0x3f803f80,0x3f803f80,0x3dc90000,0x3e953e48,0x3ef13ec4,0x3f223f0e,0xbf7bbf80,0xbf55bf6d,0xbf0ebf35,0xbe48bec4,0xbe950000,0xbf46bf0e,0xbf7fbf6d,0xbf62bf7b,
0x3f6d3f80,0x3ec43f35,0xbec40000,0xbf6dbf35,0x3ef10000,0x3f7f3f55,0x3f223f6d,0xbe953e48,0xbf55bf80,0x3e48bec4,0x3f7b3f35,0x3f0e3f6d,0xbf220000,0xbf62bf7b,0x3e95bec4,0x3f7f3f55,
0x3f353f80,0xbf350000,0xbf35bf80,0x3f350000,0x3f460000,0x3ef13f7b,0xbf75bec4,0xbdc9bf55,0xbf0ebf80,0x3f7b3ec4,0xbe483f35,0xbf55bf6d,0xbf620000,0x3dc9bf55,0x3f463f6d,0xbf75be48,
0x3ec43f80,0xbf6dbf35,0x3f6d0000,0xbec43f35,0x3f750000,0xbf223f0e,0x3dc9bf6d,0x3ef13f7b,0xbe48bf80,0x3f0e3f6d,0xbf55bf35,0x3f7b3ec4,0xbf7f0000,0x3f75be48,0xbf623ec4,0x3f46bf0e,
0x3f80,0xbf80,0x3f80,0xbf80,0x3f7f0000,0xbf75be48,0x3f623ec4,0xbf46bf0e,0x3e48bf80,0xbf0e3f6d,0x3f55bf35,0xbf7b3ec4,0xbf750000,0x3f223f0e,0xbdc9bf6d,0xbef13f7b,
0xbec43f80,0x3f6dbf35,0xbf6d0000,0x3ec43f35,0x3f620000,0xbdc9bf55,0xbf463f6d,0x3f75be48,0x3f0ebf80,0xbf7b3ec4,0x3e483f35,0x3f55bf6d,0xbf460000,0xbef13f7b,0x3f75bec4,0x3dc9bf55,
0xbf353f80,0x3f350000,0x3f35bf80,0xbf350000,0x3f220000,0x3f62bf7b,0xbe95bec4,0xbf7f3f55,0x3f55bf80,0xbe48bec4,0xbf7b3f35,0xbf0e3f6d,0xbef10000,0xbf7f3f55,0xbf223f6d,0x3e953e48,
0xbf6d3f80,0xbec43f35,0x3ec40000,0x3f6dbf35,0x3e950000,0x3f46bf0e,0x3f7fbf6d,0x3f62bf7b,0x3f7bbf80,0x3f55bf6d,0x3f0ebf35,0x3e48bec4,0xbdc90000,0xbe953e48,0xbef13ec4,0xbf223f0e,
0xbf803f80,0xbf803f80,0xbf803f80,0xbf803f80,0xbdc90000,0xbe953e48,0xbef13ec4,0xbf223f0e,0x3f7bbf80,0x3f55bf6d,0x3f0ebf35,0x3e48bec4,0x3e950000,0x3f46bf0e,0x3f7fbf6d,0x3f62bf7b,
0xbf6d3f80,0xbec43f35,0x3ec40000,0x3f6dbf35,0xbef10000,0xbf7f3f55,0xbf223f6d,0x3e953e48,0x3f55bf80,0xbe48bec4,0xbf7b3f35,0xbf0e3f6d,0x3f220000,0x3f62bf7b,0xbe95bec4,0xbf7f3f55,
0xbf353f80,0x3f350000,0x3f35bf80,0xbf350000,0xbf460000,0xbef13f7b,0x3f75bec4,0x3dc9bf55,0x3f0ebf80,0xbf7b3ec4,0x3e483f35,0x3f55bf6d,0x3f620000,0xbdc9bf55,0xbf463f6d,0x3f75be48,
0xbec43f80,0x3f6dbf35,0xbf6d0000,0x3ec43f35,0xbf750000,0x3f223f0e,0xbdc9bf6d,0xbef13f7b,0x3e48bf80,0xbf0e3f6d,0x3f55bf35,0xbf7b3ec4,0x3f7f0000,0xbf75be48,0x3f623ec4,0xbf46bf0e,
0x3f80,0xbf80,0x3f80,0xbf80,0xbf7f0000,0x3f75be48,0xbf623ec4,0x3f46bf0e,0xbe48bf80,0x3f0e3f6d,0xbf55bf35,0x3f7b3ec4,0x3f750000,0xbf223f0e,0x3dc9bf6d,0x3ef13f7b,
0x3ec43f80,0xbf6dbf35,0x3f6d0000,0xbec43f35,0xbf620000,0x3dc9bf55,0x3f463f6d,0xbf75be48,0xbf0ebf80,0x3f7b3ec4,0xbe483f35,0xbf55bf6d,0x3f460000,0x3ef13f7b,0xbf75bec4,0xbdc9bf55,
0x3f353f80,0xbf350000,0xbf35bf80,0x3f350000,0xbf220000,0xbf62bf7b,0x3e95bec4,0x3f7f3f55,0xbf55bf80,0x3e48bec4,0x3f7b3f35,0x3f0e3f6d,0x3ef10000,0x3f7f3f55,0x3f223f6d,0xbe953e48,
0x3f6d3f80,0x3ec43f35,0xbec40000,0xbf6dbf35,0xbe950000,0xbf46bf0e,0xbf7fbf6d,0xbf62bf7b,0xbf7bbf80,0xbf55bf6d,0xbf0ebf35,0xbe48bec4,0x3dc90000,0x3e953e48,0x3ef13ec4,0x3f223f0e,
0,0,0,0,0xbf7fbf80,0xbf75bf7b,0xbf62bf6d,0xbf46bf55,0xbe480000,0xbf0ebec4,0xbf55bf35,0xbf7bbf6d,0x3f753f80,0x3f223f55,0x3dc93ec4,0xbef1be48,
0x3ec40000,0x3f6d3f35,0x3f6d3f80,0x3ec43f35,0xbf62bf80,0xbdc9bf0e,0x3f463ec4,0x3f753f7b,0xbf0e0000,0xbf7bbf6d,0xbe48bf35,0x3f553ec4,0x3f463f80,0xbef13e48,0xbf75bf6d,0x3dc9bf0e,
0x3f350000,0x3f353f80,0xbf350000,0xbf35bf80,0xbf22bf80,0x3f623e48,0x3e953f6d,0xbf7fbf0e,0xbf550000,0xbe48bf6d,0x3f7b3f35,0xbf0e3ec4,0x3ef13f80,0xbf7fbf0e,0x3f22bec4,0x3e953f7b,
0x3f6d0000,0xbec43f35,0xbec4bf80,0x3f6d3f35,0xbe95bf80,0x3f463f55,0xbf7fbec4,0x3f62be48,0xbf7b0000,0x3f55bec4,0xbf0e3f35,0x3e48bf6d,0x3dc93f80,0xbe95bf7b,0x3ef13f6d,0xbf22bf55,
0x3f800000,0xbf800000,0x3f800000,0xbf800000,0x3dc9bf80,0xbe953f7b,0x3ef1bf6d,0xbf223f55,0xbf7b0000,0x3f553ec4,0xbf0ebf35,0x3e483f6d,0xbe953f80,0x3f46bf55,0xbf7f3ec4,0x3f623e48,
0x3f6d0000,0xbec4bf35,0xbec43f80,0x3f6dbf35,0x3ef1bf80,0xbf7f3f0e,0x3f223ec4,0x3e95bf7b,0xbf550000,0xbe483f6d,0x3f7bbf35,0xbf0ebec4,0xbf223f80,0x3f62be48,0x3e95bf6d,0xbf7f3f0e,
0x3f350000,0x3f35bf80,0xbf350000,0xbf353f80,0x3f46bf80,0xbef1be48,0xbf753f6d,0x3dc93f0e,0xbf0e0000,0xbf7b3f6d,0xbe483f35,0x3f55bec4,0xbf623f80,0xbdc93f0e,0x3f46bec4,0x3f75bf7b,
0x3ec40000,0x3f6dbf35,0x3f6dbf80,0x3ec4bf35,0x3f75bf80,0x3f22bf55,0x3dc9bec4,0xbef13e48,0xbe480000,0xbf0e3ec4,0xbf553f35,0xbf7b3f6d,0xbf7f3f80,0xbf753f7b,0xbf623f6d,0xbf463f55,
0,0,0,0,0x3f7fbf80,0x3f75bf7b,0x3f62bf6d,0x3f46bf55,0x3e480000,0x3f0ebec4,0x3f55bf35,0x3f7bbf6d,0xbf753f80,0xbf223f55,0xbdc93ec4,0x3ef1be48,
0xbec40000,0xbf6d3f35,0xbf6d3f80,0xbec43f35,0x3f62bf80,0x3dc9bf0e,0xbf463ec4,0xbf753f7b,0x3f0e0000,0x3f7bbf6d,0x3e48bf35,0xbf553ec4,0xbf463f80,0x3ef13e48,0x3f75bf6d,0xbdc9bf0e,
0xbf350000,0xbf353f80,0x3f350000,0x3f35bf80,0x3f22bf80,0xbf623e48,0xbe953f6d,0x3f7fbf0e,0x3f550000,0x3e48bf6d,0xbf7b3f35,0x3f0e3ec4,0xbef13f80,0x3f7fbf0e,0xbf22bec4,0xbe953f7b,
0xbf6d0000,0x3ec43f35,0x3ec4bf80,0xbf6d3f35,0x3e95bf80,0xbf463f55,0x3f7fbec4,0xbf62be48,0x3f7b0000,0xbf55bec4,0x3f0e3f35,0xbe48bf6d,0xbdc93f80,0x3e95bf7b,0xbef13f6d,0x3f22bf55,
0xbf800000,0x3f800000,0xbf800000,0x3f800000,0xbdc9bf80,0x3e953f7b,0xbef1bf6d,0x3f223f55,0x3f7b0000,0xbf553ec4,0x3f0ebf35,0xbe483f6d,0x3e953f80,0xbf46bf55,0x3f7f3ec4,0xbf623e48,
0xbf6d0000,0x3ec4bf35,0x3ec43f80,0xbf6dbf35,0xbef1bf80,0x3f7f3f0e,0xbf223ec4,0xbe95bf7b,0x3f550000,0x3e483f6d,0xbf7bbf35,0x3f0ebec4,0x3f223f80,0xbf62be48,0xbe95bf6d,0x3f7f3f0e,
0xbf350000,0xbf35bf80,0x3f350000,0x3f353f80,0xbf46bf80,0x3ef1be48,0x3f753f6d,0xbdc93f0e,0x3f0e0000,0x3f7b3f6d,0x3e483f35,0xbf55bec4,0x3f623f80,0x3dc93f0e,0xbf46bec4,0xbf75bf7b,
0xbec40000,0xbf6dbf35,0xbf6dbf80,0xbec4bf35,0xbf75bf80,0xbf22bf55,0xbdc9bec4,0x3ef13e48,0x3e480000,0x3f0e3ec4,0x3f553f35,0x3f7b3f6d,0x3f7f3f80,0x3f753f7b,0x3f623f6d,0x3f463f55,
0x3f803f80,0x3f803f80,0x3f803f80,0x3f803f80,0x3f463f35,0x3f623f55,0x3f753f6d,0x3f7f3f7b,0x3e480000,0x3f0e3ec4,0x3f553f35,0x3f7b3f6d,0xbef1bf35,0x3dc9be48,0x3f223ec4,0x3f753f55,
0xbf6dbf80,0xbec4bf35,0x3ec40000,0x3f6d3f35,0xbf75bf35,0xbf46bf7b,0x3dc9bec4,0x3f623f0e,0xbf0e0000,0xbf7bbf6d,0xbe48bf35,0x3f553ec4,0x3dc93f35,0xbf75bf0e,0xbef1bf6d,0x3f463e48,
0x3f353f80,0xbf350000,0xbf35bf80,0x3f350000,0x3f7f3f35,0xbe953f0e,0xbf62bf6d,0x3f22be48,0x3f550000,0x3e483f6d,0xbf7bbf35,0x3f0ebec4,0x3e95bf35,0x3f223f7b,0xbf7fbec4,0x3ef1bf0e,
0xbec4bf80,0x3f6d3f35,0xbf6d0000,0x3ec4bf35,0xbf62bf35,0x3f7f3e48,0xbf463ec4,0x3e95bf55,0xbf7b0000,0x3f55bec4,0xbf0e3f35,0x3e48bf6d,0xbf223f35,0x3ef1bf55,0xbe953f6d,0x3dc9bf7b,
0x3f80,0xbf80,0x3f80,0xbf80,0x3f223f35,0xbef1bf55,0x3e953f6d,0xbdc9bf7b,0x3f7b0000,0xbf55bec4,0x3f0e3f35,0xbe48bf6d,0x3f62bf35,0xbf7f3e48,0x3f463ec4,0xbe95bf55,
0x3ec4bf80,0xbf6d3f35,0x3f6d0000,0xbec4bf35,0xbe95bf35,0xbf223f7b,0x3f7fbec4,0xbef1bf0e,0xbf550000,0xbe483f6d,0x3f7bbf35,0xbf0ebec4,0xbf7f3f35,0x3e953f0e,0x3f62bf6d,0xbf22be48,
0xbf353f80,0x3f350000,0x3f35bf80,0xbf350000,0xbdc93f35,0x3f75bf0e,0x3ef1bf6d,0xbf463e48,0x3f0e0000,0x3f7bbf6d,0x3e48bf35,0xbf553ec4,0x3f75bf35,0x3f46bf7b,0xbdc9bec4,0xbf623f0e,
0x3f6dbf80,0x3ec4bf35,0xbec40000,0xbf6d3f35,0x3ef1bf35,0xbdc9be48,0xbf223ec4,0xbf753f55,0xbe480000,0xbf0e3ec4,0xbf553f35,0xbf7b3f6d,0xbf463f35,0xbf623f55,0xbf753f6d,0xbf7f3f7b,
0xbf803f80,0xbf803f80,0xbf803f80,0xbf803f80,0xbf463f35,0xbf623f55,0xbf753f6d,0xbf7f3f7b,0xbe480000,0xbf0e3ec4,0xbf553f35,0xbf7b3f6d,0x3ef1bf35,0xbdc9be48,0xbf223ec4,0xbf753f55,
0x3f6dbf80,0x3ec4bf35,0xbec40000,0xbf6d3f35,0x3f75bf35,0x3f46bf7b,0xbdc9bec4,0xbf623f0e,0x3f0e0000,0x3f7bbf6d,0x3e48bf35,0xbf553ec4,0xbdc93f35,0x3f75bf0e,0x3ef1bf6d,0xbf463e48,
0xbf353f80,0x3f350000,0x3f35bf80,0xbf350000,0xbf7f3f35,0x3e953f0e,0x3f62bf6d,0xbf22be48,0xbf550000,0xbe483f6d,0x3f7bbf35,0xbf0ebec4,0xbe95bf35,0xbf223f7b,0x3f7fbec4,0xbef1bf0e,
0x3ec4bf80,0xbf6d3f35,0x3f6d0000,0xbec4bf35,0x3f62bf35,0xbf7f3e48,0x3f463ec4,0xbe95bf55,0x3f7b0000,0xbf55bec4,0x3f0e3f35,0xbe48bf6d,0x3f223f35,0xbef1bf55,0x3e953f6d,0xbdc9bf7b,
0x3f80,0xbf80,0x3f80,0xbf80,0xbf223f35,0x3ef1bf55,0xbe953f6d,0x3dc9bf7b,0xbf7b0000,0x3f55bec4,0xbf0e3f35,0x3e48bf6d,0xbf62bf35,0x3f7f3e48,0xbf463ec4,0x3e95bf55,
0xbec4bf80,0x3f6d3f35,0xbf6d0000,0x3ec4bf35,0x3e95bf35,0x3f223f7b,0xbf7fbec4,0x3ef1bf0e,0x3f550000,0x3e483f6d,0xbf7bbf35,0x3f0ebec4,0x3f7f3f35,0xbe953f0e,0xbf62bf6d,0x3f22be48,
0x3f353f80,0xbf350000,0xbf35bf80,0x3f350000,0x3dc93f35,0xbf75bf0e,0xbef1bf6d,0x3f463e48,0xbf0e0000,0xbf7bbf6d,0xbe48bf35,0x3f553ec4,0xbf75bf35,0xbf46bf7b,0x3dc9bec4,0x3f623f0e,
0xbf6dbf80,0xbec4bf35,0x3ec40000,0x3f6d3f35,0xbef1bf35,0x3dc9be48,0x3f223ec4,0x3f753f55,0x3e480000,0x3f0e3ec4,0x3f553f35,0x3f7b3f6d,0x3f463f35,0x3f623f55,0x3f753f6d,0x3f7f3f7b,
0,0,0,0,0xbf22bf35,0xbef1bf0e,0xbe95bec4,0xbdc9be48,0xbf7bbf80,0xbf55bf6d,0xbf0ebf35,0xbe48bec4,0xbf62bf35,0xbf7fbf7b,0xbf46bf6d,0xbe95bf0e,
0xbec40000,0xbf6dbf35,0xbf6dbf80,0xbec4bf35,0x3e953f35,0xbf22be48,0xbf7fbf6d,0xbef1bf55,0x3f553f80,0xbe483ec4,0xbf7bbf35,0xbf0ebf6d,0x3f7f3f35,0x3e953f55,0xbf62bec4,0xbf22bf7b,
0x3f350000,0x3f353f80,0xbf350000,0xbf35bf80,0x3dc9bf35,0x3f753f55,0xbef13ec4,0xbf46bf7b,0xbf0ebf80,0x3f7b3ec4,0xbe483f35,0xbf55bf6d,0xbf75bf35,0x3f46be48,0x3dc93f6d,0xbf62bf55,
0xbf6d0000,0x3ec4bf35,0x3ec43f80,0xbf6dbf35,0xbef13f35,0xbdc9bf7b,0x3f223f6d,0xbf75bf0e,0x3e483f80,0xbf0ebf6d,0x3f553f35,0xbf7bbec4,0x3f463f35,0xbf62bf0e,0x3f753ec4,0xbf7fbe48,
0x3f800000,0xbf800000,0x3f800000,0xbf800000,0x3f46bf35,0xbf623f0e,0x3f75bec4,0xbf7f3e48,0x3e48bf80,0xbf0e3f6d,0x3f55bf35,0xbf7b3ec4,0xbef1bf35,0xbdc93f7b,0x3f22bf6d,0xbf753f0e,
0xbf6d0000,0x3ec43f35,0x3ec4bf80,0xbf6d3f35,0xbf753f35,0x3f463e48,0x3dc9bf6d,0xbf623f55,0xbf0e3f80,0x3f7bbec4,0xbe48bf35,0xbf553f6d,0x3dc93f35,0x3f75bf55,0xbef1bec4,0xbf463f7b,
0x3f350000,0x3f35bf80,0xbf350000,0xbf353f80,0x3f7fbf35,0x3e95bf55,0xbf623ec4,0xbf223f7b,0x3f55bf80,0xbe48bec4,0xbf7b3f35,0xbf0e3f6d,0x3e95bf35,0xbf223e48,0xbf7f3f6d,0xbef13f55,
0xbec40000,0xbf6d3f35,0xbf6d3f80,0xbec43f35,0xbf623f35,0xbf7f3f7b,0xbf463f6d,0xbe953f0e,0xbf7b3f80,0xbf553f6d,0xbf0e3f35,0xbe483ec4,0xbf223f35,0xbef13f0e,0xbe953ec4,0xbdc93e48,
0,0,0,0,0x3f22bf35,0x3ef1bf0e,0x3e95bec4,0x3dc9be48,0x3f7bbf80,0x3f55bf6d,0x3f0ebf35,0x3e48bec4,0x3f62bf35,0x3f7fbf7b,0x3f46bf6d,0x3e95bf0e,
0x3ec40000,0x3f6dbf35,0x3f6dbf80,0x3ec4bf35,0xbe953f35,0x3f22be48,0x3f7fbf6d,0x3ef1bf55,0xbf553f80,0x3e483ec4,0x3f7bbf35,0x3f0ebf6d,0xbf7f3f35,0xbe953f55,0x3f62bec4,0x3f22bf7b,
0xbf350000,0xbf353f80,0x3f350000,0x3f35bf80,0xbdc9bf35,0xbf753f55,0x3ef13ec4,0x3f46bf7b,0x3f0ebf80,0xbf7b3ec4,0x3e483f35,0x3f55bf6d,0x3f75bf35,0xbf46be48,0xbdc93f6d,0x3f62bf55,
0x3f6d0000,0xbec4bf35,0xbec43f80,0x3f6dbf35,0x3ef13f35,0x3dc9bf7b,0xbf223f6d,0x3f75bf0e,0xbe483f80,0x3f0ebf6d,0xbf553f35,0x3f7bbec4,0xbf463f35,0x3f62bf0e,0xbf753ec4,0x3f7fbe48,
0xbf800000,0x3f800000,0xbf800000,0x3f800000,0xbf46bf35,0x3f623f0e,0xbf75bec4,0x3f7f3e48,0xbe48bf80,0x3f0e3f6d,0xbf55bf35,0x3f7b3ec4,0x3ef1bf35,0x3dc93f7b,0xbf22bf6d,0x3f753f0e,
0x3f6d0000,0xbec43f35,0xbec4bf80,0x3f6d3f35,0x3f753f35,0xbf463e48,0xbdc9bf6d,0x3f623f55,0x3f0e3f80,0xbf7bbec4,0x3e48bf35,0x3f553f6d,0xbdc93f35,0xbf75bf55,0x3ef1bec4,0x3f463f7b,
0xbf350000,0xbf35bf80,0x3f350000,0x3f353f80,0xbf7fbf35,0xbe95bf55,0x3f623ec4,0x3f223f7b,0xbf55bf80,0x3e48bec4,0x3f7b3f35,0x3f0e3f6d,0xbe95bf35,0x3f223e48,0x3f7f3f6d,0x3ef13f55,
0x3ec40000,0x3f6d3f35,0x3f6d3f80,0x3ec43f35,0x3f623f35,0x3f7f3f7b,0x3f463f6d,0x3e953f0e,0x3f7b3f80,0x3f553f6d,0x3f0e3f35,0x3e483ec4,0x3f223f35,0x3ef13f0e,0x3e953ec4,0x3dc93e48};

__device__ __forceinline__ void mma_h64t(float (&d)[32], const uint32_t (&a)[4], uint64_t db, int sd) {
  asm volatile("{\n.reg .pred p;\nsetp.ne.b32 p, %37, 0;\n"
  "wgmma.mma_async.sync.aligned.m64n64k16.f32.f16.f16 {%0,%1,%2,%3,%4,%5,%6,%7,%8,%9,%10,%11,%12,%13,%14,%15,%16,%17,%18,%19,%20,%21,%22,%23,%24,%25,%26,%27,%28,%29,%30,%31}, {%32,%33,%34,%35}, %36, p, 1, 1, 1;\n}\n"
  : "+f"(d[0]),"+f"(d[1]),"+f"(d[2]),"+f"(d[3]),"+f"(d[4]),"+f"(d[5]),"+f"(d[6]),"+f"(d[7]),"+f"(d[8]),"+f"(d[9]),"+f"(d[10]),"+f"(d[11]),"+f"(d[12]),"+f"(d[13]),"+f"(d[14]),"+f"(d[15]),"+f"(d[16]),"+f"(d[17]),"+f"(d[18]),"+f"(d[19]),"+f"(d[20]),"+f"(d[21]),"+f"(d[22]),"+f"(d[23]),"+f"(d[24]),"+f"(d[25]),"+f"(d[26]),"+f"(d[27]),"+f"(d[28]),"+f"(d[29]),"+f"(d[30]),"+f"(d[31])
  : "r"(a[0]),"r"(a[1]),"r"(a[2]),"r"(a[3]),"l"(db),"r"(sd));
}
__device__ __forceinline__ void mma_h32(float (&d)[16], const uint32_t (&a)[4], uint64_t db, int sd) {
  asm volatile("{\n.reg .pred p;\nsetp.ne.b32 p, %21, 0;\n"
  "wgmma.mma_async.sync.aligned.m64n32k16.f32.f16.f16 {%0,%1,%2,%3,%4,%5,%6,%7,%8,%9,%10,%11,%12,%13,%14,%15}, {%16,%17,%18,%19}, %20, p, 1, 1, 0;\n}\n"
  : "+f"(d[0]),"+f"(d[1]),"+f"(d[2]),"+f"(d[3]),"+f"(d[4]),"+f"(d[5]),"+f"(d[6]),"+f"(d[7]),"+f"(d[8]),"+f"(d[9]),"+f"(d[10]),"+f"(d[11]),"+f"(d[12]),"+f"(d[13]),"+f"(d[14]),"+f"(d[15])
  : "r"(a[0]),"r"(a[1]),"r"(a[2]),"r"(a[3]),"l"(db),"r"(sd));
}
__device__ __forceinline__ void mma_h64(float (&d)[32], const uint32_t (&a)[4], uint64_t db, int sd) {
  asm volatile("{\n.reg .pred p;\nsetp.ne.b32 p, %37, 0;\n"
  "wgmma.mma_async.sync.aligned.m64n64k16.f32.f16.f16 {%0,%1,%2,%3,%4,%5,%6,%7,%8,%9,%10,%11,%12,%13,%14,%15,%16,%17,%18,%19,%20,%21,%22,%23,%24,%25,%26,%27,%28,%29,%30,%31}, {%32,%33,%34,%35}, %36, p, 1, 1, 0;\n}\n"
  : "+f"(d[0]),"+f"(d[1]),"+f"(d[2]),"+f"(d[3]),"+f"(d[4]),"+f"(d[5]),"+f"(d[6]),"+f"(d[7]),"+f"(d[8]),"+f"(d[9]),"+f"(d[10]),"+f"(d[11]),"+f"(d[12]),"+f"(d[13]),"+f"(d[14]),"+f"(d[15]),"+f"(d[16]),"+f"(d[17]),"+f"(d[18]),"+f"(d[19]),"+f"(d[20]),"+f"(d[21]),"+f"(d[22]),"+f"(d[23]),"+f"(d[24]),"+f"(d[25]),"+f"(d[26]),"+f"(d[27]),"+f"(d[28]),"+f"(d[29]),"+f"(d[30]),"+f"(d[31])
  : "r"(a[0]),"r"(a[1]),"r"(a[2]),"r"(a[3]),"l"(db),"r"(sd));
}
__device__ __forceinline__ void mma_h128(float (&d)[64], const uint32_t (&a)[4], uint64_t db, int sd) {
  asm volatile("{\n.reg .pred p;\nsetp.ne.b32 p, %69, 0;\n"
  "wgmma.mma_async.sync.aligned.m64n128k16.f32.f16.f16 {%0,%1,%2,%3,%4,%5,%6,%7,%8,%9,%10,%11,%12,%13,%14,%15,%16,%17,%18,%19,%20,%21,%22,%23,%24,%25,%26,%27,%28,%29,%30,%31,%32,%33,%34,%35,%36,%37,%38,%39,%40,%41,%42,%43,%44,%45,%46,%47,%48,%49,%50,%51,%52,%53,%54,%55,%56,%57,%58,%59,%60,%61,%62,%63}, {%64,%65,%66,%67}, %68, p, 1, 1, 0;\n}\n"
  : "+f"(d[0]),"+f"(d[1]),"+f"(d[2]),"+f"(d[3]),"+f"(d[4]),"+f"(d[5]),"+f"(d[6]),"+f"(d[7]),"+f"(d[8]),"+f"(d[9]),"+f"(d[10]),"+f"(d[11]),"+f"(d[12]),"+f"(d[13]),"+f"(d[14]),"+f"(d[15]),"+f"(d[16]),"+f"(d[17]),"+f"(d[18]),"+f"(d[19]),"+f"(d[20]),"+f"(d[21]),"+f"(d[22]),"+f"(d[23]),"+f"(d[24]),"+f"(d[25]),"+f"(d[26]),"+f"(d[27]),"+f"(d[28]),"+f"(d[29]),"+f"(d[30]),"+f"(d[31]),"+f"(d[32]),"+f"(d[33]),"+f"(d[34]),"+f"(d[35]),"+f"(d[36]),"+f"(d[37]),"+f"(d[38]),"+f"(d[39]),"+f"(d[40]),"+f"(d[41]),"+f"(d[42]),"+f"(d[43]),"+f"(d[44]),"+f"(d[45]),"+f"(d[46]),"+f"(d[47]),"+f"(d[48]),"+f"(d[49]),"+f"(d[50]),"+f"(d[51]),"+f"(d[52]),"+f"(d[53]),"+f"(d[54]),"+f"(d[55]),"+f"(d[56]),"+f"(d[57]),"+f"(d[58]),"+f"(d[59]),"+f"(d[60]),"+f"(d[61]),"+f"(d[62]),"+f"(d[63])
  : "r"(a[0]),"r"(a[1]),"r"(a[2]),"r"(a[3]),"l"(db),"r"(sd));
}
__device__ __forceinline__ void mma_b128(float (&d)[64], const uint32_t (&a)[4], uint64_t db, int sd) {
  asm volatile("{\n.reg .pred p;\nsetp.ne.b32 p, %69, 0;\n"
  "wgmma.mma_async.sync.aligned.m64n128k16.f32.bf16.bf16 {%0,%1,%2,%3,%4,%5,%6,%7,%8,%9,%10,%11,%12,%13,%14,%15,%16,%17,%18,%19,%20,%21,%22,%23,%24,%25,%26,%27,%28,%29,%30,%31,%32,%33,%34,%35,%36,%37,%38,%39,%40,%41,%42,%43,%44,%45,%46,%47,%48,%49,%50,%51,%52,%53,%54,%55,%56,%57,%58,%59,%60,%61,%62,%63}, {%64,%65,%66,%67}, %68, p, 1, 1, 0;\n}\n"
  : "+f"(d[0]),"+f"(d[1]),"+f"(d[2]),"+f"(d[3]),"+f"(d[4]),"+f"(d[5]),"+f"(d[6]),"+f"(d[7]),"+f"(d[8]),"+f"(d[9]),"+f"(d[10]),"+f"(d[11]),"+f"(d[12]),"+f"(d[13]),"+f"(d[14]),"+f"(d[15]),"+f"(d[16]),"+f"(d[17]),"+f"(d[18]),"+f"(d[19]),"+f"(d[20]),"+f"(d[21]),"+f"(d[22]),"+f"(d[23]),"+f"(d[24]),"+f"(d[25]),"+f"(d[26]),"+f"(d[27]),"+f"(d[28]),"+f"(d[29]),"+f"(d[30]),"+f"(d[31]),"+f"(d[32]),"+f"(d[33]),"+f"(d[34]),"+f"(d[35]),"+f"(d[36]),"+f"(d[37]),"+f"(d[38]),"+f"(d[39]),"+f"(d[40]),"+f"(d[41]),"+f"(d[42]),"+f"(d[43]),"+f"(d[44]),"+f"(d[45]),"+f"(d[46]),"+f"(d[47]),"+f"(d[48]),"+f"(d[49]),"+f"(d[50]),"+f"(d[51]),"+f"(d[52]),"+f"(d[53]),"+f"(d[54]),"+f"(d[55]),"+f"(d[56]),"+f"(d[57]),"+f"(d[58]),"+f"(d[59]),"+f"(d[60]),"+f"(d[61]),"+f"(d[62]),"+f"(d[63])
  : "r"(a[0]),"r"(a[1]),"r"(a[2]),"r"(a[3]),"l"(db),"r"(sd));
}
__device__ __forceinline__ void mma_b64t(float (&d)[32], const uint32_t (&a)[4], uint64_t db, int sd) {
  asm volatile("{\n.reg .pred p;\nsetp.ne.b32 p, %37, 0;\n"
  "wgmma.mma_async.sync.aligned.m64n64k16.f32.bf16.bf16 {%0,%1,%2,%3,%4,%5,%6,%7,%8,%9,%10,%11,%12,%13,%14,%15,%16,%17,%18,%19,%20,%21,%22,%23,%24,%25,%26,%27,%28,%29,%30,%31}, {%32,%33,%34,%35}, %36, p, 1, 1, 1;\n}\n"
  : "+f"(d[0]),"+f"(d[1]),"+f"(d[2]),"+f"(d[3]),"+f"(d[4]),"+f"(d[5]),"+f"(d[6]),"+f"(d[7]),"+f"(d[8]),"+f"(d[9]),"+f"(d[10]),"+f"(d[11]),"+f"(d[12]),"+f"(d[13]),"+f"(d[14]),"+f"(d[15]),"+f"(d[16]),"+f"(d[17]),"+f"(d[18]),"+f"(d[19]),"+f"(d[20]),"+f"(d[21]),"+f"(d[22]),"+f"(d[23]),"+f"(d[24]),"+f"(d[25]),"+f"(d[26]),"+f"(d[27]),"+f"(d[28]),"+f"(d[29]),"+f"(d[30]),"+f"(d[31])
  : "r"(a[0]),"r"(a[1]),"r"(a[2]),"r"(a[3]),"l"(db),"r"(sd));
}
__device__ __forceinline__ void mma_b32(float (&d)[16], const uint32_t (&a)[4], uint64_t db, int sd) {
  asm volatile("{\n.reg .pred p;\nsetp.ne.b32 p, %21, 0;\n"
  "wgmma.mma_async.sync.aligned.m64n32k16.f32.bf16.bf16 {%0,%1,%2,%3,%4,%5,%6,%7,%8,%9,%10,%11,%12,%13,%14,%15}, {%16,%17,%18,%19}, %20, p, 1, 1, 0;\n}\n"
  : "+f"(d[0]),"+f"(d[1]),"+f"(d[2]),"+f"(d[3]),"+f"(d[4]),"+f"(d[5]),"+f"(d[6]),"+f"(d[7]),"+f"(d[8]),"+f"(d[9]),"+f"(d[10]),"+f"(d[11]),"+f"(d[12]),"+f"(d[13]),"+f"(d[14]),"+f"(d[15])
  : "r"(a[0]),"r"(a[1]),"r"(a[2]),"r"(a[3]),"l"(db),"r"(sd));
}
__device__ __forceinline__ void mma_ss224t(float (&d)[112], uint64_t da, uint64_t db, int sd) {
  asm volatile("{\n.reg .pred p;\nsetp.ne.b32 p, %114, 0;\n"
  "wgmma.mma_async.sync.aligned.m64n224k16.f32.bf16.bf16 {%0,%1,%2,%3,%4,%5,%6,%7,%8,%9,%10,%11,%12,%13,%14,%15,%16,%17,%18,%19,%20,%21,%22,%23,%24,%25,%26,%27,%28,%29,%30,%31,%32,%33,%34,%35,%36,%37,%38,%39,%40,%41,%42,%43,%44,%45,%46,%47,%48,%49,%50,%51,%52,%53,%54,%55,%56,%57,%58,%59,%60,%61,%62,%63,%64,%65,%66,%67,%68,%69,%70,%71,%72,%73,%74,%75,%76,%77,%78,%79,%80,%81,%82,%83,%84,%85,%86,%87,%88,%89,%90,%91,%92,%93,%94,%95,%96,%97,%98,%99,%100,%101,%102,%103,%104,%105,%106,%107,%108,%109,%110,%111}, %112, %113, p, 1, 1, 0, 1;\n}\n"
  : "+f"(d[0]),"+f"(d[1]),"+f"(d[2]),"+f"(d[3]),"+f"(d[4]),"+f"(d[5]),"+f"(d[6]),"+f"(d[7]),"+f"(d[8]),"+f"(d[9]),"+f"(d[10]),"+f"(d[11]),"+f"(d[12]),"+f"(d[13]),"+f"(d[14]),"+f"(d[15]),"+f"(d[16]),"+f"(d[17]),"+f"(d[18]),"+f"(d[19]),"+f"(d[20]),"+f"(d[21]),"+f"(d[22]),"+f"(d[23]),"+f"(d[24]),"+f"(d[25]),"+f"(d[26]),"+f"(d[27]),"+f"(d[28]),"+f"(d[29]),"+f"(d[30]),"+f"(d[31]),"+f"(d[32]),"+f"(d[33]),"+f"(d[34]),"+f"(d[35]),"+f"(d[36]),"+f"(d[37]),"+f"(d[38]),"+f"(d[39]),"+f"(d[40]),"+f"(d[41]),"+f"(d[42]),"+f"(d[43]),"+f"(d[44]),"+f"(d[45]),"+f"(d[46]),"+f"(d[47]),"+f"(d[48]),"+f"(d[49]),"+f"(d[50]),"+f"(d[51]),"+f"(d[52]),"+f"(d[53]),"+f"(d[54]),"+f"(d[55]),"+f"(d[56]),"+f"(d[57]),"+f"(d[58]),"+f"(d[59]),"+f"(d[60]),"+f"(d[61]),"+f"(d[62]),"+f"(d[63]),"+f"(d[64]),"+f"(d[65]),"+f"(d[66]),"+f"(d[67]),"+f"(d[68]),"+f"(d[69]),"+f"(d[70]),"+f"(d[71]),"+f"(d[72]),"+f"(d[73]),"+f"(d[74]),"+f"(d[75]),"+f"(d[76]),"+f"(d[77]),"+f"(d[78]),"+f"(d[79]),"+f"(d[80]),"+f"(d[81]),"+f"(d[82]),"+f"(d[83]),"+f"(d[84]),"+f"(d[85]),"+f"(d[86]),"+f"(d[87]),"+f"(d[88]),"+f"(d[89]),"+f"(d[90]),"+f"(d[91]),"+f"(d[92]),"+f"(d[93]),"+f"(d[94]),"+f"(d[95]),"+f"(d[96]),"+f"(d[97]),"+f"(d[98]),"+f"(d[99]),"+f"(d[100]),"+f"(d[101]),"+f"(d[102]),"+f"(d[103]),"+f"(d[104]),"+f"(d[105]),"+f"(d[106]),"+f"(d[107]),"+f"(d[108]),"+f"(d[109]),"+f"(d[110]),"+f"(d[111])
  : "l"(da),"l"(db),"r"(sd));
}
__device__ __forceinline__ void mma_b128t(float (&d)[64], const uint32_t (&a)[4], uint64_t db, int sd) {
  asm volatile("{\n.reg .pred p;\nsetp.ne.b32 p, %69, 0;\n"
  "wgmma.mma_async.sync.aligned.m64n128k16.f32.bf16.bf16 {%0,%1,%2,%3,%4,%5,%6,%7,%8,%9,%10,%11,%12,%13,%14,%15,%16,%17,%18,%19,%20,%21,%22,%23,%24,%25,%26,%27,%28,%29,%30,%31,%32,%33,%34,%35,%36,%37,%38,%39,%40,%41,%42,%43,%44,%45,%46,%47,%48,%49,%50,%51,%52,%53,%54,%55,%56,%57,%58,%59,%60,%61,%62,%63}, {%64,%65,%66,%67}, %68, p, 1, 1, 1;\n}\n"
  : "+f"(d[0]),"+f"(d[1]),"+f"(d[2]),"+f"(d[3]),"+f"(d[4]),"+f"(d[5]),"+f"(d[6]),"+f"(d[7]),"+f"(d[8]),"+f"(d[9]),"+f"(d[10]),"+f"(d[11]),"+f"(d[12]),"+f"(d[13]),"+f"(d[14]),"+f"(d[15]),"+f"(d[16]),"+f"(d[17]),"+f"(d[18]),"+f"(d[19]),"+f"(d[20]),"+f"(d[21]),"+f"(d[22]),"+f"(d[23]),"+f"(d[24]),"+f"(d[25]),"+f"(d[26]),"+f"(d[27]),"+f"(d[28]),"+f"(d[29]),"+f"(d[30]),"+f"(d[31]),"+f"(d[32]),"+f"(d[33]),"+f"(d[34]),"+f"(d[35]),"+f"(d[36]),"+f"(d[37]),"+f"(d[38]),"+f"(d[39]),"+f"(d[40]),"+f"(d[41]),"+f"(d[42]),"+f"(d[43]),"+f"(d[44]),"+f"(d[45]),"+f"(d[46]),"+f"(d[47]),"+f"(d[48]),"+f"(d[49]),"+f"(d[50]),"+f"(d[51]),"+f"(d[52]),"+f"(d[53]),"+f"(d[54]),"+f"(d[55]),"+f"(d[56]),"+f"(d[57]),"+f"(d[58]),"+f"(d[59]),"+f"(d[60]),"+f"(d[61]),"+f"(d[62]),"+f"(d[63])
  : "r"(a[0]),"r"(a[1]),"r"(a[2]),"r"(a[3]),"l"(db),"r"(sd));
}

#define DI __device__ __forceinline__
constexpr int NCTA = 130;
constexpr int SLOT = 28672;
constexpr int OFF_R = 5 * SLOT;
constexpr int OFF_X = OFF_R + 65536;
constexpr int OFF_T = OFF_X + 16384;
constexpr int OFF_B = OFF_T + 2048;
constexpr int SMEM_BYTES = OFF_B + 256 + 768 + 1024;
constexpr int SPIN_MAX = 1 << 22;
#define PWLO 32
#define STAG 0

__device__ uint4 g_Zs[129 * 1024];
__device__ uint4 g_Wt[257 * 512];
__device__ uint4 g_Ln[16 * 8 * 1024];
__device__ uint4 g_P[16 * 8 * 3 * 1024];
__device__ unsigned g_ctr[32 * (2 + 16)];
#define TM(i)
#define TMH(i)
#define TM_START()
#define TM_END()

DI void mbar_init(uint32_t b, int n) { asm volatile("mbarrier.init.shared.b64 [%0], %1;" ::"r"(b), "r"(n)); }
DI void mbar_expect(uint32_t b, int bytes) { asm volatile("mbarrier.arrive.expect_tx.shared.b64 _, [%0], %1;" ::"r"(b), "r"(bytes) : "memory"); }
DI void mbar_arrive(uint32_t b) { asm volatile("mbarrier.arrive.shared.b64 _, [%0];" ::"r"(b) : "memory"); }
DI void mbar_wait(uint32_t b, uint32_t ph) {
  asm volatile("{\n.reg .pred p;\n.reg .u32 n;\nmov.u32 n, 0;\nLW:\nmbarrier.try_wait.parity.shared.b64 p, [%0], %1;\n@p bra LD;\n"
               "add.u32 n, n, 1;\nsetp.lt.u32 p, n, 4194304;\n@p bra LW;\ntrap;\nLD:\n}" ::"r"(b), "r"(ph) : "memory");
}
DI void mbar_wait_cluster(uint32_t b, uint32_t ph) {
  asm volatile("{\n.reg .pred p;\n.reg .u32 n;\nmov.u32 n, 0;\nLW:\nmbarrier.try_wait.parity.acquire.cluster.shared.b64 p, [%0], %1;\n@p bra LD;\n"
               "add.u32 n, n, 1;\nsetp.lt.u32 p, n, 4194304;\n@p bra LW;\ntrap;\nLD:\n}" ::"r"(b), "r"(ph) : "memory");
}
DI void mbar_arrive_l0(uint32_t b, int lane) {
  asm volatile("{\n.reg .pred p;\nsetp.eq.u32 p, %1, 0;\n@p mbarrier.arrive.shared.b64 _, [%0];\n}" ::"r"(b), "r"(lane) : "memory");
}
DI void bulk_ld(uint32_t dst, const void* src, int bytes, uint32_t bar) {
  asm volatile("cp.async.bulk.shared::cluster.global.mbarrier::complete_tx::bytes [%0], [%1], %2, [%3];" ::"r"(dst), "l"(src), "r"(bytes), "r"(bar) : "memory");
}
DI void tma3(uint32_t dst, const CUtensorMap* m, int c0, int c1, int c2, uint32_t bar) {
  asm volatile("cp.async.bulk.tensor.3d.shared::cluster.global.mbarrier::complete_tx::bytes [%0], [%1, {%3, %4, %5}], [%2];" ::"r"(dst), "l"(m), "r"(bar), "r"(c0), "r"(c1), "r"(c2) : "memory");
}
DI void l2_prefetch(const void* src, int bytes) { asm volatile("cp.async.bulk.prefetch.L2.global [%0], %1;" ::"l"(src), "r"(bytes) : "memory"); }
DI void fence_async() { asm volatile("fence.proxy.async;" ::: "memory"); }
DI void fence_async_smem() { asm volatile("fence.proxy.async.shared::cta;" ::: "memory"); }
DI void bar_sync(int id, int n) { asm volatile("bar.sync %0, %1;" ::"r"(id), "r"(n) : "memory"); }
DI void bar_arrive(int id, int n) { asm volatile("bar.arrive %0, %1;" ::"r"(id), "r"(n) : "memory"); }
DI void wg_fence() { asm volatile("wgmma.fence.sync.aligned;" ::: "memory"); }
DI void wg_commit() { asm volatile("wgmma.commit_group.sync.aligned;" ::: "memory"); }
template <int N> DI void wg_wait() { asm volatile("wgmma.wait_group.sync.aligned %0;" ::"n"(N) : "memory"); }
template <int N> DI void keep(float (&d)[N]) {
#pragma unroll
  for (int i = 0; i < N; i++) asm volatile("" : "+f"(d[i])::"memory");
}
DI uint64_t mkdesc(uint32_t addr, uint32_t lbo, uint32_t sbo, uint32_t swz) {
  return (uint64_t)((addr & 0x3FFFF) >> 4) | ((uint64_t)(lbo >> 4) << 16) | ((uint64_t)(sbo >> 4) << 32) | ((uint64_t)swz << 62);
}
DI uint64_t mkd4(uint32_t a4, uint32_t off, uint32_t lbo, uint32_t sbo, uint32_t swz) {
  return (uint64_t)(a4 + (off >> 4) + ((lbo >> 4) << 16)) | ((uint64_t)((sbo >> 4) | (swz << 30)) << 32);
}
DI uint32_t pk_h(float lo, float hi) { uint32_t r; asm("cvt.rn.f16x2.f32 %0, %1, %2;" : "=r"(r) : "f"(hi), "f"(lo)); return r; }
DI uint32_t pk_b(float lo, float hi) { uint32_t r; asm("cvt.rn.bf16x2.f32 %0, %1, %2;" : "=r"(r) : "f"(hi), "f"(lo)); return r; }
DI float blo(uint32_t v) { return __uint_as_float(v << 16); }
DI float bhi(uint32_t v) { return __uint_as_float(v & 0xffff0000u); }
DI float rbf(float v) { return blo(pk_b(v, 0.f)); }
DI uint32_t sub_b2(uint32_t a, uint32_t b) { uint32_t r; asm("sub.rn.bf16x2 %0, %1, %2;" : "=r"(r) : "r"(a), "r"(b)); return r; }
DI uint32_t add_b2(uint32_t a, uint32_t b) { uint32_t r; asm("add.rn.bf16x2 %0, %1, %2;" : "=r"(r) : "r"(a), "r"(b)); return r; }
DI uint4 lds128(uint32_t a) { uint4 v; asm volatile("ld.shared.v4.u32 {%0,%1,%2,%3}, [%4];" : "=r"(v.x), "=r"(v.y), "=r"(v.z), "=r"(v.w) : "r"(a) : "memory"); return v; }
DI uint32_t lds32(uint32_t a) { uint32_t v; asm volatile("ld.shared.u32 %0, [%1];" : "=r"(v) : "r"(a) : "memory"); return v; }
DI void sts128(uint32_t a, uint4 v) { asm volatile("st.shared.v4.u32 [%0], {%1,%2,%3,%4};" ::"r"(a), "r"(v.x), "r"(v.y), "r"(v.z), "r"(v.w) : "memory"); }
DI void sts32(uint32_t a, uint32_t v) { asm volatile("st.shared.u32 [%0], %1;" ::"r"(a), "r"(v) : "memory"); }
DI void stsm4(uint32_t a, uint32_t r0, uint32_t r1, uint32_t r2, uint32_t r3) {
  asm volatile("stmatrix.sync.aligned.m8n8.x4.shared.b16 [%0], {%1,%2,%3,%4};" ::"r"(a), "r"(r0), "r"(r1), "r"(r2), "r"(r3) : "memory");
}
DI void stsm4t(uint32_t a, uint32_t r0, uint32_t r1, uint32_t r2, uint32_t r3) {
  asm volatile("stmatrix.sync.aligned.m8n8.x4.trans.shared.b16 [%0], {%1,%2,%3,%4};" ::"r"(a), "r"(r0), "r"(r1), "r"(r2), "r"(r3) : "memory");
}
DI void ldsm4(uint32_t a, uint32_t (&r)[4]) {
  asm volatile("ldmatrix.sync.aligned.m8n8.x4.shared.b16 {%0,%1,%2,%3}, [%4];" : "=r"(r[0]), "=r"(r[1]), "=r"(r[2]), "=r"(r[3]) : "r"(a) : "memory");
}
DI unsigned ld_acq(const unsigned* p) { unsigned v; asm volatile("ld.acquire.gpu.global.u32 %0, [%1];" : "=r"(v) : "l"(p) : "memory"); return v; }
DI unsigned atom_rel(unsigned* p) { unsigned v; asm volatile("atom.add.acq_rel.gpu.global.u32 %0, [%1], 1;" : "=r"(v) : "l"(p) : "memory"); return v; }
DI void red_rel(unsigned* p) { asm volatile("red.add.release.gpu.global.u32 [%0], 1;" ::"l"(p) : "memory"); }
DI void spin_ge(const unsigned* p, unsigned target) {
  int it = 0;
  while ((int)(ld_acq(p) - target) < 0) { if (++it > SPIN_MAX) __trap(); }
}
DI uint4 ldg_v(const void* p) { uint4 v; asm volatile("ld.global.nc.v4.u32 {%0,%1,%2,%3}, [%4];" : "=r"(v.x), "=r"(v.y), "=r"(v.z), "=r"(v.w) : "l"(p)); return v; }
DI uint4 ld_rlx(const uint4* p) {
  uint4 v; asm volatile("{\n.reg .b128 t;\nld.relaxed.gpu.global.b128 t, [%4];\nmov.b128 {%0,%1,%2,%3}, t;\n}" : "=r"(v.x), "=r"(v.y), "=r"(v.z), "=r"(v.w) : "l"(p) : "memory"); return v;
}
DI void st_tag(uint4* p, uint4 v, uint32_t par) {
  asm volatile("{\n.reg .b128 t;\nmov.b128 t, {%1,%2,%3,%4};\nst.relaxed.gpu.global.b128 [%0], t;\n}" ::"l"(p), "r"((v.x & ~1u) | par), "r"(v.y), "r"(v.z), "r"(v.w) : "memory");
}
template <int N, class F> DI void pollf(uint4 (&v)[N], F addr, uint32_t par) {
#pragma unroll
  for (int i = 0; i < N; i++) v[i] = ld_rlx(addr(i));
  int it = 0;
  while (true) {
    uint32_t bad = 0;
#pragma unroll
    for (int i = 0; i < N; i++) bad |= (v[i].x ^ par);
    if (!__any_sync(0xffffffffu, bad & 1)) break;
#pragma unroll
    for (int i = 0; i < N; i++) if ((v[i].x ^ par) & 1) v[i] = ld_rlx(addr(i));
    if (++it > SPIN_MAX) __trap();
  }
#pragma unroll
  for (int i = 0; i < N; i++) v[i].x &= ~1u;
}
template <int N> DI void poll(uint4 (&v)[N], const uint4* p, int stride, uint32_t par) { pollf<N>(v, [&](int i) { return p + i * stride; }, par); }
DI void ld_frag(uint32_t (&f)[4][4], int which, int t) {
#pragma unroll
  for (int ks = 0; ks < 4; ks++) {
    uint4 v = ldg_v(reinterpret_cast<const uint4*>(c_frag) + which * 512 + ks * 128 + t);
    f[ks][0] = v.x; f[ks][1] = v.y; f[ks][2] = v.z; f[ks][3] = v.w;
  }
}
DI void ln_pair(const uint32_t (&v)[2][8], uint32_t (&o)[2][8]) {
  float s[2], ss[2], sh[2];
#pragma unroll
  for (int r = 0; r < 2; r++) sh[r] = blo(__shfl_sync(0xffffffffu, v[r][0], 0));
#pragma unroll
  for (int r = 0; r < 2; r++) {
    s[r] = 0.f; ss[r] = 0.f;
#pragma unroll
    for (int i = 0; i < 8; i++) {
      float a = blo(v[r][i]) - sh[r], b = bhi(v[r][i]) - sh[r];
      s[r] += a + b; ss[r] = fmaf(a, a, fmaf(b, b, ss[r]));
    }
  }
#pragma unroll
  for (int d = 16; d >= 1; d >>= 1)
#pragma unroll
    for (int r = 0; r < 2; r++) { s[r] += __shfl_xor_sync(0xffffffffu, s[r], d); ss[r] += __shfl_xor_sync(0xffffffffu, ss[r], d); }
#pragma unroll
  for (int r = 0; r < 2; r++) {
    float ms = s[r] * (1.f / 512.f);
    float var = fmaxf(fmaf(-ms, ms, ss[r] * (1.f / 512.f)), 0.f);
    float mean = ms + sh[r];
    uint32_t m2 = pk_b(mean, mean);
    float sd, inv;
    asm("sqrt.approx.f32 %0, %1;" : "=f"(sd) : "f"(rbf(rbf(var) + 1e-5f)));
    asm("rcp.approx.f32 %0, %1;" : "=f"(inv) : "f"(rbf(sd)));
#pragma unroll
    for (int i = 0; i < 8; i++) { uint32_t d2 = sub_b2(v[r][i], m2); o[r][i] = pk_b(blo(d2) * inv, bhi(d2) * inv); }
  }
}
DI float silu_f(float x) { float t; float h = 0.5f * x; asm("tanh.approx.f32 %0, %1;" : "=f"(t) : "f"(h)); return fmaf(h, t, h); }

enum { B_T0 = 0, B_T1, B_WT, B_FA, B_FW = B_FA + 4, B_EM = B_FW + 5, B_PW = B_EM + 5, B_PW2, B_RF, B_RX, B_N = B_RF + 10, B_WR = B_N };

DI void add_h(uint32_t (&a)[16], uint32_t sH, int chunk0, int e) {
  uint32_t v[8];
#pragma unroll
  for (int t = 0; t < 8; t++) v[t] = lds32((sH + chunk0 * 16) ^ (t << 4));
  if (e) {
#pragma unroll
    for (int t = 0; t < 8; t++) asm volatile("add.rn.bf16x2 %0, %0, %1;" : "+r"(a[2 * t + 1]) : "r"(v[t]));
  } else {
#pragma unroll
    for (int t = 0; t < 8; t++) asm volatile("add.rn.bf16x2 %0, %0, %1;" : "+r"(a[2 * t]) : "r"(v[t]));
  }
}
DI void send_half(const float* a, bool hw, uint32_t sH, int chunk0, int e, uint32_t rx, uint32_t rbar) {
  uint32_t k[16];
#pragma unroll
  for (int i = 0; i < 16; i++) k[i] = pk_b(a[2 * i], a[2 * i + 1]);
  if (hw) add_h(k, sH, chunk0, e);
#pragma unroll
  for (int i = 0; i < 4; i++)
    asm volatile("st.async.weak.shared::cluster.mbarrier::complete_tx::bytes.v4.b32 [%0], {%1,%2,%3,%4}, [%5];" ::"r"(rx + i * 512),
                 "r"(k[4 * i]), "r"(k[4 * i + 1]), "r"(k[4 * i + 2]), "r"(k[4 * i + 3]), "r"(rbar) : "memory");
}
DI void acc8(float* s, uint4 v) {
  s[0] += blo(v.x); s[1] += bhi(v.x); s[2] += blo(v.y); s[3] += bhi(v.y); s[4] += blo(v.z); s[5] += bhi(v.z); s[6] += blo(v.w); s[7] += bhi(v.w);
}

DI void pair_send(const float* acc, const float* own, uint32_t (&k)[16], int step, int sl, int e, bool hw, uint32_t sH, uint32_t rx, uint32_t rbar) {
  send_half(acc, hw, sH, (2 * sl + (e ^ 1)) * 8, e, rx + step * 16384, rbar + step * 8);
#pragma unroll
  for (int i = 0; i < 16; i++) k[i] = pk_b(own[2 * i], own[2 * i + 1]);
  if (hw) add_h(k, sH, (2 * sl + e) * 8, e);
}
DI void pair_fin(uint32_t (&k)[16], int step, int sl, int e, bool hw, uint32_t sH, uint32_t lx, uint32_t lbar, uint4* gP, uint32_t par) {
  mbar_wait_cluster(lbar + step * 8, 0);
#pragma unroll
  for (int i = 0; i < 4; i++) {
    const uint4 v = lds128(lx + step * 16384 + i * 512);
    k[4 * i] = add_b2(k[4 * i], v.x); k[4 * i + 1] = add_b2(k[4 * i + 1], v.y); k[4 * i + 2] = add_b2(k[4 * i + 2], v.z); k[4 * i + 3] = add_b2(k[4 * i + 3], v.w);
  }
  uint4* dst = gP + (2 * sl * 3 + step) * 1024;
#pragma unroll
  for (int i = 0; i < 4; i++) st_tag(dst + i * 256, make_uint4(k[4 * i], k[4 * i + 1], k[4 * i + 2], k[4 * i + 3]), par);
}

__global__ void __cluster_dims__(2, 1, 1) __launch_bounds__(384, 1)
gfnet_kernel(const __grid_constant__ CUtensorMap tmW1, const __grid_constant__ CUtensorMap tmW2,
             const uint4* __restrict__ x, const char* __restrict__ wr, const char* __restrict__ wi,
             const char* __restrict__ w1raw, const char* __restrict__ w2raw, uint4* __restrict__ out) {
  extern __shared__ char smem_raw[];
  const uint32_t sb = ((uint32_t)__cvta_generic_to_shared(smem_raw) + 1023u) & ~1023u;
  const uint32_t bars = sb + OFF_B, sb4 = (sb & 0x3FFFF) >> 4;
  const int tid = threadIdx.x, c = blockIdx.x, lane = tid & 31;
  const int g = __shfl_sync(0xffffffffu, tid >> 7, 0), w = (tid >> 5) & 3, r = lane >> 2, q = lane & 3, t128 = tid & 127;
  const int rb = c >> 3, cj = c & 7, sg = cj >> 1;
#define BAR(i) (bars + 8 * (i))

  if (c == 129) return;
  TM_START();
  const uint32_t sEp = bars + 8 * (B_WR + 1);

  if (g == 2) {
    asm volatile("setmaxnreg.dec.sync.aligned.u32 40;");
    if (w == 0) {
      if (lane < B_N && lane != B_WT) mbar_init(BAR(lane), (lane >= B_EM && lane < B_EM + 5) ? 8 : (lane == B_RF || lane == B_RF + 5) ? 4 : (lane == B_PW || lane == B_PW2) ? 2 : 1);
      asm volatile("fence.mbarrier_init.release.cluster;" ::: "memory");
      fence_async_smem();
      __syncwarp();
      if (lane == 0) {
        mbar_expect(BAR(B_T0), 2048);  bulk_ld(sb + OFF_T, c_smt, 2048, BAR(B_T0));
        for (int i = 0; i < 8; i++) mbar_expect(BAR(B_RX + i + (i >> 2)), 8192);
      }
      unsigned ep;
      asm volatile("ld.relaxed.gpu.global.u32 %0, [%1];" : "=r"(ep) : "l"(&g_ctr[0]) : "memory");
      ep += 1;
      if (lane == 0) sts32(sEp, ep);
      __syncwarp();
      if (lane == 0) { mbar_expect(BAR(B_T1), 32768); bulk_ld(sb + OFF_R, c_smt + 512, 32768, BAR(B_T1)); }
      bar_sync(0, 384);
      if (c >= 128) return;
      bar_sync(7, 352);
      if (lane == 0) { l2_prefetch(w1raw + (size_t)c * 14336, 14336); l2_prefetch(w2raw + (size_t)c * 14336, 14336); }
      mbar_wait(BAR(B_WT), 0);
      if (lane == 0)
        for (int i = 0; i < 3; i++) { mbar_expect(BAR(B_FW + i), SLOT); tma3(sb + i * SLOT, &tmW1, 0, i * 64, cj * 7, BAR(B_FW + i)); }
      __syncwarp();
      bar_sync(1, 384);
      if (lane == 0)
        for (int i = 3; i < 5; i++) { mbar_expect(BAR(B_FW + i), SLOT); tma3(sb + i * SLOT, &tmW1, 0, i * 64, cj * 7, BAR(B_FW + i)); }
      __syncwarp();
      bar_sync(6, 288);
      if (lane == 0) {
        TMH(4);
        red_rel(&g_ctr[32 * (2 + rb)]);
        TMH(5);
        spin_ge(&g_ctr[32 * (2 + rb)], ep * 8);
        TMH(6);
        asm volatile("fence.proxy.async.global;" ::: "memory");
        const uint4* lnsrc = g_Ln + (size_t)rb * 8 * 1024;
        mbar_expect(BAR(B_FA + 3), 16384); bulk_ld(sb + OFF_R + 3 * 16384, lnsrc + 3 * 1024, 16384, BAR(B_FA + 3));
        for (int i = 0; i <= 10; i++) {
          const int sl = i % 5, it = i + 5;
          mbar_wait(BAR(B_EM + sl), (i / 5) & 1);
          if (i < 4) { mbar_expect(BAR(B_FA + i), 16384); bulk_ld(sb + OFF_R + i * 16384, lnsrc + (i + 4) * 1024, 16384, BAR(B_FA + i)); }
          mbar_expect(BAR(B_FW + sl), SLOT);
          if (it < 8) tma3(sb + sl * SLOT, &tmW1, 0, it * 64, cj * 7, BAR(B_FW + sl));
          else
            for (int h = 0; h < 2; h++)
              tma3(sb + sl * SLOT + h * 14336, &tmW2, 0, cj * 224 + (it & 1) * 112, ((sg + 1 + ((it - 8) >> 1)) & 3) * 2 + ((cj & 1) ^ h ^ 1), BAR(B_FW + sl));
        }
      }
    } else {
      const uint32_t sWr = sb + 4 * SLOT;
      unsigned ep = 0;
      if (c < 128) {
        const int st = (((c >> 2) * 514) & ~15) + (c & 3) * 2 * 16448;
#pragma unroll
        for (int n = 0; n < 11; n++) {
          const int idx = tid - 288 + 96 * n, row = idx / 33;
          const char* src = (row < 16 ? wr : wi) + st + (((row & 14) << 2) + (row & 1)) * 16448 + (idx - row * 33) * 16;
          asm volatile("cp.async.cg.shared.global [%0], [%1], 16;" ::"r"(sWr + idx * 16), "l"(src) : "memory");
        }
      }
      if (c < 128) {
#pragma unroll 4
        for (int i = tid - 288; i < 1026; i += 96) st_tag(g_Zs + (i >> 3) * 1024 + c * 8 + (i & 7), make_uint4(0, 0, 0, 0), 0);
      }
      if (tid == 288) { mbar_init(BAR(B_WT), 32); TMH(7); }
      __syncwarp();
      bar_arrive(0, 384);
      if (c < 128) {
        if (tid == 288) asm volatile("ld.relaxed.gpu.global.u32 %0, [%1];" : "=r"(ep) : "l"(&g_ctr[0]) : "memory");
        asm volatile("cp.async.wait_all;" ::: "memory");
        bar_sync(5, 96);
        if (tid == 288) TMH(0);
        const int pc = lane & 3;
        const int ko = (c >> 2) & 7;
        uint4* dst = g_Wt + c * 4 + (pc ^ ((c >> 1) & 3)) - ko * 512;
#pragma unroll 2
        for (int kp = (tid - 288) >> 2; kp < 132; kp += 24) {
          const uint32_t ra = sWr + pc * 4 * 528 + kp * 4;
          uint32_t lo[4], hi[4];
#pragma unroll
          for (int m = 0; m < 4; m++) { lo[m] = lds32(ra + m * 528); hi[m] = lds32(ra + m * 528 + 16 * 528); }
          if ((unsigned)(2 * kp - ko) <= 256u) dst[kp * 1024] = make_uint4(__byte_perm(lo[0], hi[0], 0x5410), __byte_perm(lo[1], hi[1], 0x5410), __byte_perm(lo[2], hi[2], 0x5410), __byte_perm(lo[3], hi[3], 0x5410));
          if ((unsigned)(2 * kp + 1 - ko) <= 256u) dst[kp * 1024 + 512] = make_uint4(__byte_perm(lo[0], hi[0], 0x7632), __byte_perm(lo[1], hi[1], 0x7632), __byte_perm(lo[2], hi[2], 0x7632), __byte_perm(lo[3], hi[3], 0x7632));
        }
        __syncwarp();
        if (w == 1) bar_arrive(1, 384);
        bar_sync(5, 96);
      }
      if (w >= 2 && c < 128) {
        bar_sync(7, 352);
        const uint32_t np = (lds32(sEp) & 1) ^ 1;
        const int t = tid - 320;
#pragma unroll 2
        for (int n = 0; n < 6; n++) st_tag(g_Ln + (rb * 8 + (n >> 1)) * 1024 + ((n & 1) * 64 + 8 * cj) * 8 + t, make_uint4(0, 0, 0, 0), np);
        __syncwarp();
        mbar_arrive_l0(BAR(B_PW), lane);
        bar_sync(1, 384);
#pragma unroll 4
        for (int n = 47; n >= PWLO; n--) st_tag(g_P + ((rb * 8 + (cj & 1) + 2 * ((sg + 1 + (n >> 4)) & 3)) * 3 + (n >> 4)) * 1024 + (n & 15) * 64 + t, make_uint4(0, 0, 0, 0), np);
        __syncwarp();
        mbar_arrive_l0(BAR(B_PW2), lane);
      }
      if (w == 1) {
        if (lane == 0) {
          if (c >= 128) asm volatile("ld.relaxed.gpu.global.u32 %0, [%1];" : "=r"(ep) : "l"(&g_ctr[0]) : "memory");
          ep += 1;
          TMH(1);
          if (c < 128) red_rel(&g_ctr[32]);
          TMH(2);
          spin_ge(&g_ctr[32], ep * 128);
          TMH(3);
        }
        __syncwarp();
        const uint4* src = g_Wt + (c < 128 ? (2 * c + 1) * 512 : 0) + lane;
#pragma unroll 8
        for (int n = 0; n < 32; n++) asm volatile("cp.async.cg.shared.global [%0], [%1], 16;" ::"r"(sb + OFF_X + n * 512 + lane * 16), "l"(src + n * 32) : "memory");
        asm volatile("cp.async.mbarrier.arrive.noinc.shared.b64 [%0];" ::"r"(BAR(B_WT)) : "memory");
        asm volatile("cp.async.wait_all;" ::: "memory");
      }
    }
    return;
  }

  TM(0);
  float twr[4], twi[4];
  if (c < 128) {
    const int kc = c >> 5, b = 2 * (c & 31) + g;
    const int s0 = 64 * (4 * kc + w) + b;
    uint32_t xv[2][8];
#pragma unroll
    for (int rr = 0; rr < 2; rr++)
#pragma unroll
      for (int hh = 0; hh < 2; hh++) {
        uint4 v = ldg_v(x + (size_t)(s0 + rr * 1024) * 64 + hh * 32 + lane);
        xv[rr][hh * 4] = v.x; xv[rr][hh * 4 + 1] = v.y; xv[rr][hh * 4 + 2] = v.z; xv[rr][hh * 4 + 3] = v.w;
      }
    uint32_t fa[4][4];
#pragma unroll
    for (int i = 0; i < 4; i++) {
      const int p = ((8 * w + r) * (8 * i + 2 * q) + 16) % 32 - 16, p1 = ((8 * w + r) * (8 * i + 2 * q + 1) + 16) % 32 - 16;
      float s0, c0, s1, c1;
      __sincosf((float)p * (6.283185307179586f / 32.f), &s0, &c0); __sincosf((float)p1 * (6.283185307179586f / 32.f), &s1, &c1);
      const uint32_t cc = pk_h(c0, c1), ss = pk_h(s0, s1);
      fa[i >> 1][2 * (i & 1)] = cc; fa[i >> 1][2 * (i & 1) + 1] = ss ^ 0x80008000u; fa[2 + (i >> 1)][2 * (i & 1)] = ss; fa[2 + (i >> 1)][2 * (i & 1) + 1] = cc;
    }
#pragma unroll
    for (int i = 0; i < 4; i++) {
      int p = ((8 * w + r) * (8 * (i >> 1) + 2 * q + (i & 1)) + 256) % 512 - 256;
      float sn, cn; __sincosf((float)p * (6.283185307179586f / 512.f), &sn, &cn);
      twr[i] = cn * 0.04419417382415922f; twi[i] = -sn * 0.04419417382415922f;
    }
    uint32_t ln[2][8];
    ln_pair(xv, ln);
    TM(1);
    const uint32_t sA = sb + OFF_R + 32768 + g * 8192;
#pragma unroll
    for (int rr = 0; rr < 2; rr++)
#pragma unroll
      for (int hh = 0; hh < 2; hh++) {
        const int n1 = hh * 16 + (lane >> 1);
        uint4 v;
        v.x = pk_h(blo(ln[rr][hh * 4]), bhi(ln[rr][hh * 4])); v.y = pk_h(blo(ln[rr][hh * 4 + 1]), bhi(ln[rr][hh * 4 + 1]));
        v.z = pk_h(blo(ln[rr][hh * 4 + 2]), bhi(ln[rr][hh * 4 + 2])); v.w = pk_h(blo(ln[rr][hh * 4 + 3]), bhi(ln[rr][hh * 4 + 3]));
        sts128(sA + (4 * rr + (n1 >> 3)) * 1024 + (2 * w + (lane & 1)) * 128 + (n1 & 7) * 16, v);
      }
    fence_async_smem();
    bar_sync(2 + g, 128);
    float d[32];
    wg_fence();
#pragma unroll
    for (int ks = 0; ks < 4; ks++) mma_h64t(d, fa[ks], mkd4((sA & 0x3FFFF) >> 4, ks * 2048, 1024, 128, 0), ks);
    wg_commit();
    bar_sync(0, 384);
    mbar_wait(BAR(B_T0), 0);
    wg_wait<0>(); keep(d);
    uint32_t a2[4][4];
#pragma unroll
    for (int j = 0; j < 4; j++)
#pragma unroll
      for (int h = 0; h < 2; h++) {
        const int o = 8 * j + 4 * h;
        a2[j][2 * h] = pk_h(d[o] * twr[2 * h] - d[o + 2] * twi[2 * h], d[o + 1] * twr[2 * h + 1] - d[o + 3] * twi[2 * h + 1]);
        a2[j][2 * h + 1] = pk_h(d[o] * twi[2 * h] + d[o + 2] * twr[2 * h], d[o + 1] * twi[2 * h + 1] + d[o + 3] * twr[2 * h + 1]);
      }
    float e[4][16];
    wg_fence();
#pragma unroll
    for (int j = 0; j < 4; j++) mma_h32(e[j], a2[j], mkd4(sb4, OFF_T, 128, 256, 0), 0);
    wg_commit(); wg_wait<0>();
#pragma unroll
    for (int j = 0; j < 4; j++) keep(e[j]);
    const uint32_t sS = sb + 3 * SLOT;
#pragma unroll
    for (int i = 0; i < 4; i++) {
      const int o = 4 * (i >> 1) + (i & 1);
      const int k = 8 * w + r + 32 * (8 * (i >> 1) + 2 * q + (i & 1));
      const uint4 v = make_uint4(pk_h(e[0][o] + e[0][o + 10], e[0][o + 2] - e[0][o + 8]), pk_h(e[1][o] + e[1][o + 10], e[1][o + 2] - e[1][o + 8]),
                                 pk_h(e[2][o] + e[2][o + 10], e[2][o + 2] - e[2][o + 8]), pk_h(e[3][o] + e[3][o + 10], e[3][o + 2] - e[3][o + 8]));
      const int pos = (k == 0) ? 1024 + g : (k <= 256 ? (k - 1) * 4 + g : (511 - k) * 4 + 2 + g);
      sts128(sS + ((pos ^ ((pos >> 8) & 3)) << 4), v);
      if (k == 256) sts128(sS + (((pos + 2) ^ 3) << 4), v);
    }
    bar_sync(4, 256);
#pragma unroll
    for (int i = 0; i < 4; i++) st_tag(g_Zs + (i * 32 + (tid >> 3)) * 1024 + c * 8 + (tid & 7), lds128(sS + (((i * 256 + tid) ^ i) << 4)), 1);
    if (tid < 2) st_tag(g_Zs + 128 * 1024 + c * 8 + tid, lds128(sS + ((1024 + tid) << 4)), 1);
    TM(2);
  } else {
    bar_sync(0, 384);
    if (g == 1) return;
  }
  asm volatile("setmaxnreg.inc.sync.aligned.u32 232;");
  const uint32_t par = lds32(sEp) & 1;
  const int kcol = (c >= 128) ? 0 : 2 * c + 1 + g;
  const uint32_t sZ = sb + OFF_R + 49152 + g * 8192, sW = sb + OFF_X + g * 8192, sG = sb + OFF_R + 32768 + g * 8192;
  uint32_t xr[2][8];
  {
    uint32_t f1[4][4], f4[4][4];
    ld_frag(f1, 1, t128);
    ld_frag(f4, (kcol & 255) == 0 ? 3 : 2, t128);
    float tr[16], ti[16];
#pragma unroll
    for (int i = 0; i < 16; i++) {
      int p = ((8 * w + r) * (8 * (i >> 1) + 2 * q + (i & 1)) + 1024) % 2048 - 1024;
      float sn, cn; __sincosf((float)p * (6.283185307179586f / 2048.f), &sn, &cn);
      tr[i] = cn * 0.02209708691207961f; ti[i] = -sn * 0.02209708691207961f;
    }
    {
      uint4 z[4];
      poll<4>(z, g_Zs + c * 1024 + (t128 >> 2) * 8 + (c >= 128 ? (t128 & 1) : g * 4 + (t128 & 3)), 256, 1);
      if (c < 128) bar_arrive(7, 352);
#pragma unroll
      for (int i = 0; i < 4; i++) sts128(sZ + ((t128 >> 1) & 1) * 4096 + i * 1024 + ((t128 >> 2) * 2 + (t128 & 1)) * 16, z[i]);
      fence_async_smem();
      mbar_wait(BAR(B_T1), 0);
      bar_sync(2 + g, 128);
    }
    TM(3);
    float d[32];
    wg_fence();
#pragma unroll
    for (int ks = 0; ks < 4; ks++) mma_h64(d, f1[ks], mkd4((sZ & 0x3FFFF) >> 4, ks * 2048, 1024, 128, 0), ks);
    wg_commit(); wg_wait<0>(); keep(d);
    uint32_t a[4][4];
#pragma unroll
    for (int t = 0; t < 8; t++) {
      const int o = 4 * t;
      a[t >> 1][2 * (t & 1)] = pk_h(d[o] * tr[2 * t] - d[o + 2] * ti[2 * t], d[o + 1] * tr[2 * t + 1] - d[o + 3] * ti[2 * t + 1]);
      a[t >> 1][2 * (t & 1) + 1] = pk_h(d[o] * ti[2 * t] + d[o + 2] * tr[2 * t], d[o + 1] * ti[2 * t + 1] + d[o + 3] * tr[2 * t + 1]);
    }
    float e[64];
    wg_fence();
#pragma unroll
    for (int ks = 0; ks < 4; ks++) mma_h128(e, a[ks], mkd4(sb4, OFF_R + ks * 4096, 2048, 128, 0), ks);
    wg_commit();
    mbar_wait(BAR(B_WT), 0);
    TM(17);
    uint32_t wv[16];
#pragma unroll
    for (int i = 0; i < 4; i++) {
      uint4 v = lds128(sW + t128 * 64 + ((i ^ ((t128 >> 1) & 3)) << 4));
      wv[4 * i] = v.x; wv[4 * i + 1] = v.y; wv[4 * i + 2] = v.z; wv[4 * i + 3] = v.w;
    }
    wg_wait<0>(); keep(e);
#pragma unroll
    for (int t = 0; t < 8; t++) {
      const int o = 4 * t;
      float r0 = e[o] + e[o + 34], i0 = e[o + 2] - e[o + 32], r1 = e[o + 1] + e[o + 35], i1 = e[o + 3] - e[o + 33];
      float a0 = blo(wv[2 * t]), b0 = bhi(wv[2 * t]), a1 = blo(wv[2 * t + 1]), b1 = bhi(wv[2 * t + 1]);
      a[t >> 1][2 * (t & 1)] = pk_b(r0 * a0 - i0 * b0, r1 * a1 - i1 * b1);
      a[t >> 1][2 * (t & 1) + 1] = pk_b(r0 * b0 + i0 * a0, r1 * b1 + i1 * a1);
    }
    wg_fence();
#pragma unroll
    for (int ks = 0; ks < 4; ks++) mma_b128(e, a[ks], mkd4(sb4, OFF_R + 16384 + ks * 4096, 2048, 128, 0), ks);
    wg_commit(); wg_wait<0>(); keep(e);
#pragma unroll
    for (int t = 0; t < 8; t++) {
      const int o = 4 * t;
      float r0 = e[o] - e[o + 34], i0 = e[o + 2] + e[o + 32], r1 = e[o + 1] - e[o + 35], i1 = e[o + 3] + e[o + 33];
      a[t >> 1][2 * (t & 1)] = pk_b(r0 * tr[2 * t] + i0 * ti[2 * t], r1 * tr[2 * t + 1] + i1 * ti[2 * t + 1]);
      a[t >> 1][2 * (t & 1) + 1] = pk_b(i0 * tr[2 * t] - r0 * ti[2 * t], i1 * tr[2 * t + 1] - r1 * ti[2 * t + 1]);
    }
#pragma unroll
    for (int tt = 0; tt < 4; tt++)
      stsm4(sG + (2 * w + ((lane >> 3) & 1)) * 1024 + (2 * tt + (lane >> 4)) * 128 + (lane & 7) * 16, a[tt][0], a[tt][1], a[tt][2], a[tt][3]);
    fence_async_smem();
    bar_sync(2 + g, 128);
    wg_fence();
#pragma unroll
    for (int ks = 0; ks < 4; ks++) mma_b64t(d, f4[ks], mkd4((sG & 0x3FFFF) >> 4, ks * 2048, 1024, 128, 0), ks);
    wg_commit();
    if (c < 128) {
      const int s0 = 64 * rb + 8 * cj + 4 * g + w;
#pragma unroll
      for (int rr = 0; rr < 2; rr++)
#pragma unroll
        for (int hh = 0; hh < 2; hh++) {
          uint4 v = ldg_v(x + (size_t)(s0 + rr * 1024) * 64 + hh * 32 + lane);
          xr[rr][hh * 4] = v.x; xr[rr][hh * 4 + 1] = v.y; xr[rr][hh * 4 + 2] = v.z; xr[rr][hh * 4 + 3] = v.w;
        }
    }
    wg_wait<0>(); keep(d);
    TM(18);
    {
      const int mi = lane >> 3, li = lane & 7;
#pragma unroll
      for (int tt = 0; tt < 4; tt++) {
        const int pos = ((8 * (w & 1) + li) * 8 + 2 * tt + (mi >> 1)) * 4 + (w >> 1) * 2 + (mi & 1);
        stsm4(sZ + ((pos ^ li) << 4), pk_b(d[8 * tt], d[8 * tt + 1]), pk_b(d[8 * tt + 2], d[8 * tt + 3]), pk_b(d[8 * tt + 4], d[8 * tt + 5]), pk_b(d[8 * tt + 6], d[8 * tt + 7]));
      }
      bar_sync(2 + g, 128);
#pragma unroll
      for (int i = 0; i < 4; i++) {
        const int pos = i * 128 + t128;
        const uint4 v = lds128(sZ + ((pos ^ ((pos >> 5) & 7)) << 4));
        if (c < 128 || !(pos & 2)) st_tag(g_Zs + c * 1024 + (pos >> 2) * 8 + g * 4 + (pos & 3), v, 0);
      }
    }
    TM(4);
  }
  if (c >= 128) return;
  {
    uint32_t fc[4][4];
    ld_frag(fc, 4, t128);
    bar_sync(4, 256);
    const int W = tid >> 5, mi = lane >> 3, li = lane & 7;
    const uint32_t sO = sb + OFF_R + 49152;
    {
      uint4 z[4];
      const int k0 = 64 * W + 8 * (q >> 1) + r;
      const uint4* zp = g_Zs + c * 8 + (q & 1);
      pollf<4>(z, [&](int i) { const int k = k0 + 16 * i, km = (k <= 256 ? k : 512 - k) - 1;
                               return zp + (k == 0 ? 128 * 1024 : (km >> 1) * 1024 + (km & 1) * 4 + (k > 256 ? 2 : 0)); }, 0);
      bar_arrive(1, 384);
      TM(5);
      const int j = 2 * mi + (li & 1), cp = (li >> 1) & 1, h = li >> 2;
#pragma unroll
      for (int i = 0; i < 4; i++) {
        const int k1 = 4 * W + i;
        stsm4t(sO + (j >> 2) * 9344 + (4 * cp + (k1 >> 3)) * 1168 + (2 * (j & 3) + h) * 144 + (k1 & 7) * 16, z[i].x, z[i].y, z[i].z, z[i].w);
      }
    }
    fence_async_smem();
    bar_sync(4, 256);
    float d[32];
    wg_fence();
#pragma unroll
    for (int ks = 0; ks < 4; ks++) mma_b64t(d, fc[ks], mkd4(((sO + g * 9344) & 0x3FFFF) >> 4, ks * 2336, 1168, 144, 0), ks);
    wg_commit(); wg_wait<0>(); keep(d);
    uint32_t a2[4][4];
#pragma unroll
    for (int j = 0; j < 4; j++)
#pragma unroll
      for (int h = 0; h < 2; h++) {
        const int o = 8 * j + 4 * h;
        a2[j][2 * h] = pk_b(d[o] * twr[2 * h] + d[o + 2] * twi[2 * h], d[o + 1] * twr[2 * h + 1] + d[o + 3] * twi[2 * h + 1]);
        a2[j][2 * h + 1] = pk_b(d[o + 2] * twr[2 * h] - d[o] * twi[2 * h], d[o + 3] * twr[2 * h + 1] - d[o + 1] * twi[2 * h + 1]);
      }
    float e[4][16];
    wg_fence();
#pragma unroll
    for (int j = 0; j < 4; j++) mma_b32(e[j], a2[j], mkd4(sb4, OFF_T + 1024, 128, 256, 0), 0);
    wg_commit(); wg_wait<0>();
#pragma unroll
    for (int j = 0; j < 4; j++) keep(e[j]);
    const uint32_t sY = sb + OFF_R + 32768 + g * 8192;
    {
      const int t = mi >> 1, cc = mi & 1, chi = 4 * (8 * t + li) + w;
      const uint32_t ya = sY + cc * 1024 + ((chi ^ ((chi >> 3) & 7)) << 4);
#pragma unroll
      for (int j = 0; j < 4; j++)
        stsm4t(ya + j * 2048, pk_b(e[j][0] - e[j][10], e[j][1] - e[j][11]), pk_b(e[j][2] + e[j][8], e[j][3] + e[j][9]),
               pk_b(e[j][4] - e[j][14], e[j][5] - e[j][15]), pk_b(e[j][6] + e[j][12], e[j][7] + e[j][13]));
    }
    bar_sync(4, 256);
    uint32_t hv[2][8], ln[2][8];
#pragma unroll
    for (int rr = 0; rr < 2; rr++)
#pragma unroll
      for (int hh = 0; hh < 2; hh++) {
        const int chi = hh * 32 + lane;
        uint4 v = lds128(sY + w * 2048 + rr * 1024 + ((chi ^ ((chi >> 3) & 7)) << 4));
        hv[rr][hh * 4] = add_b2(xr[rr][hh * 4], v.x); hv[rr][hh * 4 + 1] = add_b2(xr[rr][hh * 4 + 1], v.y);
        hv[rr][hh * 4 + 2] = add_b2(xr[rr][hh * 4 + 2], v.z); hv[rr][hh * 4 + 3] = add_b2(xr[rr][hh * 4 + 3], v.w);
      }
    ln_pair(hv, ln);
    TM(21);
    mbar_wait(BAR(B_PW), 0);
#pragma unroll
    for (int hh = 0; hh < 2; hh++)
#pragma unroll
      for (int rr = 0; rr < 2; rr++) {
        const int m = rr * 64 + 8 * cj + 4 * g + w;
        const int idx = (rb * 8 + hh * 4 + (lane >> 3)) * 1024 + m * 8 + ((lane & 7) ^ (m & 7));
        const uint4 lv = make_uint4(ln[rr][hh * 4], ln[rr][hh * 4 + 1], ln[rr][hh * 4 + 2], ln[rr][hh * 4 + 3]);
        st_tag(g_Ln + idx, lv, (hh == 0 && lane < 24) ? par : (lv.x & 1));
        sts128(sb + OFF_X + rr * 8192 + (4 * g + w) * 1024 + (((hh * 32 + lane) ^ (4 * g + w)) << 4), make_uint4(hv[rr][hh * 4], hv[rr][hh * 4 + 1], hv[rr][hh * 4 + 2], hv[rr][hh * 4 + 3]));
      }
    TM(6);
    bar_arrive(6, 288);
  }
  uint32_t hf[14][4];
  const int e = cj & 1;
  uint4* gP = g_P + (size_t)(rb * 8 + e) * 3 * 1024 + tid;
  const uint32_t lx = sb + OFF_R + (tid >> 5) * 2048 + lane * 16, lbar = BAR(B_RX + 5 * g), sH = sb + OFF_X + g * 8192 + r * 1040 + q * 4;
  uint32_t rx, rbar;
  asm volatile("mapa.shared::cluster.u32 %0, %1, %2;" : "=r"(rx) : "r"(lx), "r"(e ^ 1));
  asm volatile("mapa.shared::cluster.u32 %0, %1, %2;" : "=r"(rbar) : "r"(lbar), "r"(e ^ 1));
  {
    float acc[112];
#pragma unroll 1
    for (int i = 0; i < 8; i++) {
      mbar_wait(BAR(B_FW + i % 5), (i / 5) & 1);
      if (i >= 3) mbar_wait(BAR(B_FA + (i & 3)), i == 7);
      else {
        uint4 z[4];
        poll<4>(z, g_Ln + rb * 8192 + i * 1024 + g * 512 + t128, 128, par);
#pragma unroll
        for (int n = 0; n < 4; n++) sts128(sb + OFF_R + i * 16384 + g * 8192 + (n * 128 + t128) * 16, z[n]);
        fence_async_smem();
        bar_sync(2 + g, 128);
        if (i == 0 && g == 1) bar_sync(8, 256);
      }
      const uint32_t a0 = sb + OFF_R + (i & 3) * 16384 + g * 8192, b0 = sb + (i % 5) * SLOT;
      wg_fence();
#pragma unroll
      for (int ks = 0; ks < 4; ks++) mma_ss224t(acc, mkd4((a0 & 0x3FFFF) >> 4, ks * 32, 16, 1024, 1), mkd4((b0 & 0x3FFFF) >> 4, ks * 1024, 4096, 512, 2), (i | ks));
      wg_commit();
      if (i > 0) { wg_wait<1>(); mbar_arrive_l0(BAR(B_EM + (i - 1) % 5), lane); }
      if (i == STAG && g == 0) bar_arrive(8, 256);
    }
    wg_wait<0>(); keep(acc);
    mbar_arrive_l0(BAR(B_EM + 2), lane);
    if (lane == 0) asm volatile("mbarrier.arrive.relaxed.cluster.shared::cluster.b64 _, [%0];" ::"r"(rbar - 8) : "memory");
    TM(8);
    if (g == 1) bar_sync(9, 256);
#pragma unroll
    for (int ks = 0; ks < 14; ks++)
#pragma unroll
      for (int i = 0; i < 4; i++) {
        uint32_t p = pk_b(acc[8 * ks + 2 * i], acc[8 * ks + 2 * i + 1]);
        hf[ks][i] = pk_b(silu_f(blo(p)), silu_f(bhi(p)));
      }
  }
  {
    uint32_t m = ~0u;
#pragma unroll
    for (int i = 0; i < 56; i++) m &= hf[i >> 2][i & 3];
    const int dep = (m == ~0u);
    if (g == 0) bar_arrive(9 + dep, 256); else bar_sync(10 + dep, 256);
  }
  TM(9);
  const bool hw = (w == sg);
  uint32_t k1[16];
  {
    float accA[64], accB[64];
    uint32_t k0[16];
#pragma unroll
    for (int it = 0; it < 4; it++) {
      mbar_wait(BAR(B_FW + (3 + it) % 5), it < 2);
      wg_fence();
#pragma unroll
      for (int ks = 0; ks < 7; ks++) mma_b128t(it < 2 ? accA : accB, hf[(it & 1) * 7 + ks], mkd4(sb4, ((3 + it) % 5) * SLOT + ks * 2048, 14336, 1024, 1), (it & 1) | ks);
      wg_commit();
      if (it == 3) bar_arrive(10 + g, 256);
      if (it > 0) { wg_wait<1>(); mbar_arrive_l0(BAR(B_EM + (2 + it) % 5), lane); }
    }
    keep(accA);
    TM(15);
    mbar_wait_cluster(lbar - 8, 0);
    pair_send(accA, accA + 32, k0, 0, (sg + 1) & 3, e, hw, sH, rx, rbar);
    wg_wait<0>(); keep(accB);
    pair_send(accB, accB + 32, k1, 1, (sg + 2) & 3, e, hw, sH, rx, rbar);
    TM(16);
    pair_fin(k0, 0, (sg + 1) & 3, e, hw, sH, lx, lbar, gP, par);
  }
  TM(10);
  {
    float q0[32], q1[32], p0[32], p1[32], s[32];
    uint32_t k[16];
    if (g == 0) bar_sync(11, 256);
    mbar_wait(BAR(B_FW + 2), 0);
    mbar_wait(BAR(B_FW + 3), 0);
    TM(19);
    wg_fence();
#pragma unroll
    for (int ks = 0; ks < 14; ks++) mma_b64t(q0, hf[ks], mkd4(sb4, (2 + ks / 7) * SLOT + (ks % 7) * 2048, 14336, 1024, 1), ks);
    wg_commit();
#pragma unroll
    for (int ks = 0; ks < 14; ks++) mma_b64t(q1, hf[ks], mkd4(sb4, (2 + ks / 7) * SLOT + 14336 + (ks % 7) * 2048, 14336, 1024, 1), ks);
    wg_commit();
    wg_wait<1>(); keep(q0);
    send_half(q0, hw, sH, (2 * ((sg + 3) & 3) + (e ^ 1)) * 8, e, rx + 2 * 16384, rbar + 16);
    TM(22);
    pair_fin(k1, 1, (sg + 2) & 3, e, hw, sH, lx, lbar, gP, par);
    __syncwarp();
    mbar_wait(BAR(B_FW + 4), 0);
    mbar_wait(BAR(B_FW + 0), 1);
    TM(20);
    wg_fence();
#pragma unroll
    for (int ks = 0; ks < 14; ks++) mma_b64t(p0, hf[ks], mkd4(sb4, (ks < 7 ? 4 : 0) * SLOT + (ks % 7) * 2048, 14336, 1024, 1), ks);
    wg_commit();
    wg_wait<1>(); keep(q1);
#pragma unroll
    for (int i = 0; i < 16; i++) k[i] = pk_b(q1[2 * i], q1[2 * i + 1]);
    if (hw) add_h(k, sH, (2 * ((sg + 3) & 3) + e) * 8, e);
    mbar_wait(BAR(B_PW2), 0);
    pair_fin(k, 2, (sg + 3) & 3, e, hw, sH, lx, lbar, gP, par);
    TM(14);
    __syncwarp();
    const uint4* gp = gP + 2 * sg * 3 * 1024;
    uint4 v[8];
#pragma unroll
    for (int i = 0; i < 8; i++) v[i] = ld_rlx(gp + i * 256);
    wg_wait<0>(); keep(p0);
    send_half(p0, hw, sH, (cj ^ 1) * 8, e, rx + 3 * 16384, rbar + 24);
    TM(23);
    wg_fence();
#pragma unroll
    for (int ks = 0; ks < 14; ks++) mma_b64t(p1, hf[ks], mkd4(sb4, (ks < 7 ? 4 : 0) * SLOT + 14336 + (ks % 7) * 2048, 14336, 1024, 1), ks);
    wg_commit();
    uint4 z[4];
#pragma unroll
    for (int i = 0; i < 4; i++) z[i] = ld_rlx(gp + 2048 + i * 256);
    uint32_t bad = 0;
#pragma unroll
    for (int i = 0; i < 8; i++) { bad |= v[i].x ^ par; v[i].x &= ~1u; }
    if (__any_sync(0xffffffffu, bad & 1)) poll<8>(v, gp, 256, par);
#pragma unroll
    for (int i = 0; i < 32; i++) s[i] = 0.f;
#pragma unroll
    for (int i = 0; i < 8; i++) acc8(s + (i & 3) * 8, v[i]);
    TM(11);
    mbar_wait_cluster(lbar + 24, 0);
#pragma unroll
    for (int i = 0; i < 4; i++) acc8(s + i * 8, lds128(lx + 3 * 16384 + i * 512));
    bad = 0;
#pragma unroll
    for (int i = 0; i < 4; i++) { bad |= z[i].x ^ par; z[i].x &= ~1u; }
    if (__any_sync(0xffffffffu, bad & 1)) poll<4>(z, gp + 2048, 256, par);
#pragma unroll
    for (int i = 0; i < 4; i++) acc8(s + i * 8, z[i]);
    TM(12);
    wg_wait<0>(); keep(p1);
    const uint32_t sO = sb + OFF_R + (tid >> 5) * 2048;
#pragma unroll
    for (int i = 0; i < 16; i++) k[i] = pk_b(s[2 * i] + p1[2 * i], s[2 * i + 1] + p1[2 * i + 1]);
    if (hw) add_h(k, sH, cj * 8, e);
#pragma unroll
    for (int t = 0; t < 4; t++) stsm4(sO + (lane & 15) * 128 + (((2 * t + (lane >> 4)) ^ (lane & 7)) << 4), k[4 * t], k[4 * t + 1], k[4 * t + 2], k[4 * t + 3]);
    __syncwarp();
#pragma unroll
    for (int i = 0; i < 4; i++) {
      const int row = 4 * i + (lane >> 3);
      uint4 o = lds128(sO + row * 128 + (((lane & 7) ^ (row & 7)) << 4));
      out[(size_t)(g * 1024 + rb * 64 + 16 * w + row) * 64 + cj * 8 + (lane & 7)] = o;
    }
    TM(13);
    if (c == 0 && tid == 0) g_ctr[0] = lds32(sEp);
    TM_END();
  }
}

typedef CUresult (*EncFn)(CUtensorMap*, CUtensorMapDataType, cuuint32_t, void*, const cuuint64_t*, const cuuint64_t*, const cuuint32_t*,
                          const cuuint32_t*, CUtensorMapInterleave, CUtensorMapSwizzle, CUtensorMapL2promotion, CUtensorMapFloatOOBfill);

extern "C" void kernel_launch(void* const* d_in, const int* in_sizes, int n_in, void* d_out, int out_size) {
  static EncFn enc = nullptr;
  if (!enc) {
    void* fn = nullptr; cudaDriverEntryPointQueryResult st;
    cudaGetDriverEntryPoint("cuTensorMapEncodeTiled", &fn, cudaEnableDefault, &st);
    enc = (EncFn)fn;
    cudaFuncSetAttribute(gfnet_kernel, cudaFuncAttributeMaxDynamicSharedMemorySize, SMEM_BYTES);
  }
  CUtensorMap m1, m2;
  {
    cuuint64_t dims[3] = {32, 512, 56}, str[2] = {3584, 64};
    cuuint32_t box[3] = {32, 64, 7}, es[3] = {1, 1, 1};
    enc(&m1, CU_TENSOR_MAP_DATA_TYPE_BFLOAT16, 3, d_in[4], dims, str, box, es, CU_TENSOR_MAP_INTERLEAVE_NONE, CU_TENSOR_MAP_SWIZZLE_64B,
        CU_TENSOR_MAP_L2_PROMOTION_L2_128B, CU_TENSOR_MAP_FLOAT_OOB_FILL_NONE);
  }
  {
    cuuint64_t dims[3] = {64, 1792, 8}, str[2] = {1024, 128};
    cuuint32_t box[3] = {64, 112, 1}, es[3] = {1, 1, 1};
    enc(&m2, CU_TENSOR_MAP_DATA_TYPE_BFLOAT16, 3, d_in[5], dims, str, box, es, CU_TENSOR_MAP_INTERLEAVE_NONE, CU_TENSOR_MAP_SWIZZLE_128B,
        CU_TENSOR_MAP_L2_PROMOTION_L2_128B, CU_TENSOR_MAP_FLOAT_OOB_FILL_NONE);
  }
  gfnet_kernel<<<NCTA, 384, SMEM_BYTES>>>(m1, m2, (const uint4*)d_in[0], (const char*)d_in[1], (const char*)d_in[2],
                                          (const char*)d_in[4], (const char*)d_in[5], (uint4*)d_out);
}
```
